```python
import torch

def _softmax(x, axis=-1):
    return torch.softmax(x, dim=axis)
def _gelu(x):
    return torch.nn.functional.gelu(x, approximate="tanh")
def _silu(x):
    return torch.nn.functional.silu(x)
def _sigmoid(x):
    return torch.sigmoid(x)
def _layernorm(x, axis=-1, eps=1e-5):
    m = x.mean(dim=axis, keepdim=True)
    v = x.var(dim=axis, keepdim=True, unbiased=False)
    return (x - m) / torch.sqrt(v + eps)
def _scatter_add(tgt, idx, src, axis=0):
    return tgt.clone().index_add_(axis, idx, src)
def _segment_sum(src, seg, n):
    out = torch.zeros((n,) + src.shape[1:], dtype=src.dtype)
    return out.index_add_(0, seg, src)
def _pad(x, pw):
    flat = tuple(v for pair in reversed(pw) for v in pair)
    return torch.nn.functional.pad(x, flat)

kernel_name = 'standalone__cheap_equivariant_egnn__graph'

def setup_inputs():

    _w = (lambda a: (lambda t: t.to(torch.bfloat16) if t.is_floating_point() else t)(torch.as_tensor(a)))
    N, deg, D, De = 10000, 16, 256, max(4, 1)
    E = N * deg
    return {
        "h": _w((lambda *s: torch.randn(*s, dtype=torch.bfloat16) * 0.2)(N, D)),
        "pos": _w((lambda *s: torch.randn(*s, dtype=torch.bfloat16) * 0.4)(N, 3)),
        "e_attr": _w((lambda *s: torch.randn(*s, dtype=torch.bfloat16) * 0.4)(E, De)),
        "src": _w((lambda lo, hi, *s: torch.randint(lo, hi, s))(0, N, E).to(torch.int64)),
        "dst": _w((lambda lo, hi, *s: torch.randint(lo, hi, s))(0, N, E).to(torch.int64)),
        "w_e": _w(0.1 * (lambda *s: torch.randn(*s, dtype=torch.bfloat16) * 0.4)(2 * D + 1 + De, D)),
        "w_x": _w(0.1 * (lambda *s: torch.randn(*s, dtype=torch.bfloat16) * 0.2)(D, 1)),
        "w_h": _w(0.1 * (lambda *s: torch.randn(*s, dtype=torch.bfloat16) * 0.2)(2 * D, D)),
    }

def reference(h, pos, e_attr, src, dst, w_e, w_x, w_h):
    N, D = h.shape[0], h.shape[1]
    diff = pos[dst] - pos[src]
    dist2 = torch.sum(diff * diff, axis=-1, keepdims=True)
    e_in = torch.concatenate([h[dst], h[src], dist2, e_attr], axis=-1)
    m_ij = _silu(e_in @ w_e)
    coord_scale = m_ij @ w_x
    pos_new = pos + _segment_sum(diff * coord_scale, dst, N)
    m_i = _segment_sum(m_ij, dst, N)
    h_new = h + _silu(torch.concatenate([h, m_i], axis=-1) @ w_h)
    return h_new, pos_new
```

```cpp
#include <cuda_runtime.h>
#include <cuda_bf16.h>
#include <cuda.h>
#include <stdint.h>
#include <type_traits>
#include <climits>

namespace {

constexpr int NN = 10000, NE = 160000, DD = 256;
constexpr int NCTA = 132, NPC = 76, EPC = 1216;
constexpr int NTHREADS = 640;
constexpr int REG_CON = 112, REG_AUX = 32;
constexpr int CAP = 2048;
constexpr int XCAP = 128;

constexpr int OFF_W = 0;
constexpr int OFF_H = 3 * 32768;
constexpr int OFF_MT = OFF_H + 40960;
constexpr int OFF_V = OFF_MT + 40960;
constexpr int OFF_EV = OFF_V + 5 * 4096;
constexpr int OFF_REC = OFF_EV + 512 + 8192 + 128;
constexpr int OFF_PRD = OFF_REC + CAP * 4 - 96;
constexpr int OFF_PD = OFF_PRD + CAP - 32;
constexpr int MB_V = OFF_PD + 1024;
constexpr int MB_H = MB_V + 256;
constexpr int MB_W = MB_H + 32;
constexpr int MB_W2 = MB_W + 96;
constexpr int MB_BR = MB_W2 + 32;
constexpr int MB_B = MB_BR + 8;
constexpr int MB_META = MB_B + 8;
constexpr int OFF_CNT = MB_META + 16;
constexpr int OFF_BCNT = OFF_CNT + 544;
constexpr int OFF_SP = OFF_BCNT + 96;
constexpr int OFF_DUM = OFF_SP + 96;
constexpr int OFF_X = OFF_DUM + 128;
constexpr int SMEM_BYTES = OFF_X + XCAP * 8;
static_assert(SMEM_BYTES <= 232448, "smem");
static_assert(OFF_BCNT % 16 == 0 && OFF_V + NCTA * 256 <= OFF_PD, "layout");

__device__ uint4 g_B[NN * 32];
__device__ uint4 g_in[2][NCTA * NCTA * 8];
__device__ float2 g_U[NCTA * 16 * 120];
__device__ uint32_t g_cnt[2];
__device__ uint32_t g_sidx[NE + NCTA * 1280];
#define TIM(i)
#define TIMDUMP()
#define TIMX 0

__device__ __forceinline__ void mbar_init(uint32_t a, uint32_t n) { asm volatile("mbarrier.init.shared.b64 [%0], %1;" ::"r"(a), "r"(n) : "memory"); }
__device__ __forceinline__ void mbar_expect(uint32_t a, uint32_t bytes) { asm volatile("mbarrier.arrive.expect_tx.shared.b64 _, [%0], %1;" ::"r"(a), "r"(bytes) : "memory"); }
__device__ __forceinline__ void mbar_arrive(uint32_t a) { asm volatile("mbarrier.arrive.shared.b64 _, [%0];" ::"r"(a) : "memory"); }
__device__ __forceinline__ bool mbar_try(uint32_t a, uint32_t par) {
    uint32_t ok;
    asm volatile("{.reg .pred p; mbarrier.try_wait.parity.shared.b64 p, [%1], %2; selp.u32 %0,1,0,p;}" : "=r"(ok) : "r"(a), "r"(par) : "memory");
    return ok;
}
constexpr int SPIN = 1 << 20;
__device__ __forceinline__ void mbar_wait(uint32_t a, uint32_t par) {
    if (mbar_try(a, par)) return;
    for (int i = 0; i < SPIN; i++) if (mbar_try(a, par)) return;
}
__device__ __forceinline__ void bar_sync(int id, int n) { asm volatile("bar.sync %0, %1;" ::"r"(id), "r"(n) : "memory"); }
__device__ __forceinline__ void fence_async() { asm volatile("fence.proxy.async.shared::cta;" ::: "memory"); }
__device__ __forceinline__ void tma2d(uint32_t dst, const CUtensorMap* m, int x, int y, uint32_t bar) {
    asm volatile("cp.async.bulk.tensor.2d.shared::cluster.global.mbarrier::complete_tx::bytes [%0], [%1, {%3, %4}], [%2];"
                 ::"r"(dst), "l"(m), "r"(bar), "r"(x), "r"(y) : "memory");
}
__device__ __forceinline__ void cp16(uint32_t dst, const void* src) { asm volatile("cp.async.cg.shared.global [%0], [%1], 16;" ::"r"(dst), "l"(src) : "memory"); }
__device__ __forceinline__ void cp_commit() { asm volatile("cp.async.commit_group;" ::: "memory"); }
template <int N> __device__ __forceinline__ void cp_wait() { asm volatile("cp.async.wait_group %0;" ::"n"(N) : "memory"); }
__device__ __forceinline__ uint32_t lds32(uint32_t a) { uint32_t v; asm volatile("ld.shared.u32 %0,[%1];" : "=r"(v) : "r"(a) : "memory"); return v; }
__device__ __forceinline__ uint32_t lds16(uint32_t a) { uint32_t v; asm volatile("ld.shared.u16 %0,[%1];" : "=r"(v) : "r"(a) : "memory"); return v; }
__device__ __forceinline__ uint4 lds128(uint32_t a) { uint4 v; asm volatile("ld.shared.v4.u32 {%0,%1,%2,%3},[%4];" : "=r"(v.x), "=r"(v.y), "=r"(v.z), "=r"(v.w) : "r"(a) : "memory"); return v; }
__device__ __forceinline__ void sts32(uint32_t a, uint32_t v) { asm volatile("st.shared.u32 [%0],%1;" ::"r"(a), "r"(v) : "memory"); }
__device__ __forceinline__ void sts128(uint32_t a, uint4 v) { asm volatile("st.shared.v4.u32 [%0],{%1,%2,%3,%4};" ::"r"(a), "r"(v.x), "r"(v.y), "r"(v.z), "r"(v.w) : "memory"); }
__device__ __forceinline__ uint32_t atoms_inc(uint32_t a) { uint32_t v; asm volatile("atom.shared.add.u32 %0,[%1],1;" : "=r"(v) : "r"(a) : "memory"); return v; }
__device__ __forceinline__ uint32_t ld_acq(const uint32_t* p) { uint32_t v; asm volatile("ld.acquire.gpu.global.u32 %0,[%1];" : "=r"(v) : "l"(p) : "memory"); return v; }
__device__ __forceinline__ uint32_t ld_rlx(const uint32_t* p) { uint32_t v; asm volatile("ld.relaxed.gpu.global.u32 %0,[%1];" : "=r"(v) : "l"(p) : "memory"); return v; }
__device__ __forceinline__ void reds_inc(uint32_t a) { asm volatile("red.shared.add.u32 [%0],1;" ::"r"(a) : "memory"); }
__device__ __forceinline__ uint4 ld_pkt(const uint4* p) {
    uint4 v;
    asm volatile("{.reg .b128 t; ld.relaxed.gpu.global.b128 t,[%4]; mov.b128 {%0,%1,%2,%3},t;}" : "=r"(v.x), "=r"(v.y), "=r"(v.z), "=r"(v.w) : "l"(p) : "memory");
    return v;
}
__device__ __forceinline__ void st_pkt(uint4* p, uint4 v) {
    asm volatile("{.reg .b128 t; mov.b128 t,{%1,%2,%3,%4}; st.relaxed.gpu.global.b128 [%0],t;}" ::"l"(p), "r"(v.x), "r"(v.y), "r"(v.z), "r"(v.w) : "memory");
}
__device__ __forceinline__ void sts32_gt(uint32_t a, uint32_t v, int n, int k) { asm volatile("{.reg .pred p; setp.gt.s32 p,%2,%3; @p st.shared.u32 [%0],%1;}" ::"r"(a), "r"(v), "r"(n), "r"(k) : "memory"); }
__device__ __forceinline__ void sts8_gt(uint32_t a, uint32_t v, int n, int k) { asm volatile("{.reg .pred p; setp.gt.s32 p,%2,%3; @p st.shared.u8 [%0],%1;}" ::"r"(a), "r"(v), "r"(n), "r"(k) : "memory"); }
__device__ __forceinline__ uint32_t lds8(uint32_t a) { uint32_t v; asm volatile("ld.shared.u8 %0,[%1];" : "=r"(v) : "r"(a) : "memory"); return v; }
__device__ __forceinline__ uint2 lds64(uint32_t a) { uint2 v; asm volatile("ld.shared.v2.u32 {%0,%1},[%2];" : "=r"(v.x), "=r"(v.y) : "r"(a) : "memory"); return v; }
__device__ __forceinline__ bool elect() { uint32_t p; asm volatile("{.reg .pred p; elect.sync _|p, 0xffffffff; selp.u32 %0,1,0,p;}" : "=r"(p)); return p; }
__device__ __forceinline__ void arrive_one(uint32_t a) { __syncwarp(); asm volatile("{.reg .pred p; elect.sync _|p, 0xffffffff; @p mbarrier.arrive.shared.b64 _, [%0];}" ::"r"(a) : "memory"); }
template <int DO> __device__ __forceinline__ void cp_row(uint32_t dst, const void* base, uint32_t row) {
    asm volatile("{.reg .b64 a; mad.wide.u32 a,%6,512,%1;\n\t"
                 "cp.async.cg.shared.global [%0+%2], [a], 16;\n\tcp.async.cg.shared.global [%0+%3], [a+128], 16;\n\t"
                 "cp.async.cg.shared.global [%0+%4], [a+256], 16;\n\tcp.async.cg.shared.global [%0+%5], [a+384], 16;}"
                 ::"r"(dst), "l"(base), "n"(DO), "n"(DO + 8192), "n"(DO + 16384), "n"(DO + 24576), "r"(row) : "memory");
}
__device__ __forceinline__ void l2_prefetch(const void* p, uint32_t bytes) { asm volatile("cp.async.bulk.prefetch.L2.global [%0], %1;" ::"l"(p), "r"(bytes) : "memory"); }
__device__ __forceinline__ void fence_gpu() { asm volatile("fence.acq_rel.gpu;" ::: "memory"); }
__device__ __forceinline__ void ldsm4t(uint32_t* r, uint32_t a) {
    asm volatile("ldmatrix.sync.aligned.m8n8.x4.trans.shared.b16 {%0,%1,%2,%3},[%4];" : "=r"(r[0]), "=r"(r[1]), "=r"(r[2]), "=r"(r[3]) : "r"(a) : "memory");
}
__device__ __forceinline__ void ldsm4t_keep(uint32_t* r, uint32_t a, uint32_t nz) {
    asm volatile("{.reg .pred p; setp.ne.u32 p,%5,0; @p ldmatrix.sync.aligned.m8n8.x4.trans.shared.b16 {%0,%1,%2,%3},[%4];}"
                 : "+r"(r[0]), "+r"(r[1]), "+r"(r[2]), "+r"(r[3]) : "r"(a), "r"(nz) : "memory");
}
__device__ __forceinline__ void stsm4t(uint32_t a, uint32_t r0, uint32_t r1, uint32_t r2, uint32_t r3) {
    asm volatile("stmatrix.sync.aligned.m8n8.x4.trans.shared.b16 [%0],{%1,%2,%3,%4};" ::"r"(a), "r"(r0), "r"(r1), "r"(r2), "r"(r3) : "memory");
}
__device__ __forceinline__ void stsm4(uint32_t a, uint32_t r0, uint32_t r1, uint32_t r2, uint32_t r3) {
    asm volatile("stmatrix.sync.aligned.m8n8.x4.shared.b16 [%0],{%1,%2,%3,%4};" ::"r"(a), "r"(r0), "r"(r1), "r"(r2), "r"(r3) : "memory");
}
__device__ __forceinline__ uint32_t movm(uint32_t x) { uint32_t y; asm volatile("movmatrix.sync.aligned.m8n8.trans.b16 %0,%1;" : "=r"(y) : "r"(x)); return y; }
__device__ __forceinline__ uint32_t pack(float lo, float hi) { uint32_t r; asm("cvt.rn.bf16x2.f32 %0,%1,%2;" : "=r"(r) : "f"(hi), "f"(lo)); return r; }
__device__ __forceinline__ uint32_t packh(float lo, float hi) { uint32_t r; asm("cvt.rn.f16x2.f32 %0,%1,%2;" : "=r"(r) : "f"(hi), "f"(lo)); return r; }
__device__ __forceinline__ uint32_t halve_h2(uint32_t a) { uint32_t r; asm("mul.rn.f16x2 %0,%1,%2;" : "=r"(r) : "r"(a), "r"(0x38003800u)); return r; }
__device__ __forceinline__ uint32_t tanh_h2(uint32_t x) { uint32_t t; asm("tanh.approx.f16x2 %0,%1;" : "=r"(t) : "r"(x)); return t; }
__device__ __forceinline__ uint32_t fma_h2(uint32_t x, uint32_t t) { uint32_t r; asm("fma.rn.f16x2 %0,%1,%2,%1;" : "=r"(r) : "r"(x), "r"(t)); return r; }
__device__ __forceinline__ uint32_t silu_half_h2(uint32_t x) { uint32_t t, r; asm("tanh.approx.f16x2 %0,%1;" : "=r"(t) : "r"(x)); asm("fma.rn.f16x2 %0,%1,%2,%1;" : "=r"(r) : "r"(x), "r"(t)); return r; }
__device__ __forceinline__ float bflo(uint32_t v) { return __uint_as_float(v << 16); }
__device__ __forceinline__ float bfhi(uint32_t v) { return __uint_as_float(v & 0xffff0000u); }
__device__ __forceinline__ float rbf(float x) { return bflo(pack(x, 0.f)); }
__device__ __forceinline__ float silu_half(float x) { float t; asm("tanh.approx.f32 %0,%1;" : "=f"(t) : "f"(x)); return fmaf(x, t, x); }
__device__ __forceinline__ uint32_t hmul2(uint32_t a, uint32_t b) { uint32_t r; asm("mul.rn.bf16x2 %0,%1,%2;" : "=r"(r) : "r"(a), "r"(b)); return r; }
__device__ __forceinline__ uint32_t hsub2(uint32_t a, uint32_t b) { uint32_t r; asm("sub.rn.bf16x2 %0,%1,%2;" : "=r"(r) : "r"(a), "r"(b)); return r; }
__device__ __forceinline__ uint32_t hadd2(uint32_t a, uint32_t b) { uint32_t r; asm("add.rn.bf16x2 %0,%1,%2;" : "=r"(r) : "r"(a), "r"(b)); return r; }

__device__ __forceinline__ void wg_fence() { asm volatile("wgmma.fence.sync.aligned;" ::: "memory"); }
__device__ __forceinline__ void wg_commit() { asm volatile("wgmma.commit_group.sync.aligned;" ::: "memory"); }
template <int N> __device__ __forceinline__ void wg_wait() { asm volatile("wgmma.wait_group.sync.aligned %0;" ::"n"(N) : "memory"); }
template <int N> __device__ __forceinline__ void pin(float* r) {
#pragma unroll
    for (int i = 0; i < N; i++) asm volatile("" : "+f"(r[i])::"memory");
}
template <int N> __device__ __forceinline__ void pin(uint32_t* r) {
#pragma unroll
    for (int i = 0; i < N; i++) asm volatile("" : "+r"(r[i])::"memory");
}
#define D4(o) "+f"(d[o]), "+f"(d[o + 1]), "+f"(d[o + 2]), "+f"(d[o + 3])
template <int TB, int ACC, int BHI> __device__ __forceinline__ void wss80(float* d, uint32_t a, uint32_t b) {
    asm volatile("{.reg .b64 da, db; mov.b64 da,{%40,0x40000040}; mov.b64 db,{%41,%44}; wgmma.mma_async.sync.aligned.m64n80k16.f32.bf16.bf16 "
                 "{%0,%1,%2,%3,%4,%5,%6,%7,%8,%9,%10,%11,%12,%13,%14,%15,%16,%17,%18,%19,%20,%21,%22,%23,%24,%25,%26,%27,%28,%29,%30,%31,%32,%33,%34,%35,%36,%37,%38,%39},"
                 "da,db,%42,1,1,1,%43;}"
                 : D4(0), D4(4), D4(8), D4(12), D4(16), D4(20), D4(24), D4(28), D4(32), D4(36)
                 : "r"(a), "r"(b), "n"(ACC), "n"(TB), "n"(BHI));
}
template <int TB, int ACC, int HI> __device__ __forceinline__ void wrs32(float* d, const uint32_t* a, uint32_t lo) {
    asm volatile("{.reg .b64 ds; mov.b64 ds,{%20,%23}; wgmma.mma_async.sync.aligned.m64n32k16.f32.f16.f16 "
                 "{%0,%1,%2,%3,%4,%5,%6,%7,%8,%9,%10,%11,%12,%13,%14,%15},{%16,%17,%18,%19},ds,%21,1,1,%22;}"
                 : D4(0), D4(4), D4(8), D4(12)
                 : "r"(a[0]), "r"(a[1]), "r"(a[2]), "r"(a[3]), "r"(lo), "n"(ACC), "n"(TB), "n"(HI));
}
__device__ __forceinline__ void wrs32h(uint32_t* d, const uint32_t* a, uint32_t lo) {
    asm volatile("{.reg .b64 ds; mov.b64 ds,{%12,8}; wgmma.mma_async.sync.aligned.m64n32k16.f16.f16.f16 {%0,%1,%2,%3,%4,%5,%6,%7},{%8,%9,%10,%11},ds,1,1,1,0;}"
                 : "+r"(d[0]), "+r"(d[1]), "+r"(d[2]), "+r"(d[3]), "+r"(d[4]), "+r"(d[5]), "+r"(d[6]), "+r"(d[7])
                 : "r"(a[0]), "r"(a[1]), "r"(a[2]), "r"(a[3]), "r"(lo));
}
#undef D4

struct Params {
    const int* dst; const int* src; const __nv_bfloat16* pos; uint32_t* cnt; uint4* in; const uint2* ea;
    const __nv_bfloat16* w_e; const __nv_bfloat16* w_x; const __nv_bfloat16* w_h; __nv_bfloat16* out; const uint4* h; const uint4* B; float2* U;
};

template <int TB, int FIRST> __device__ __forceinline__ void gemm_chunk(float* acc, uint32_t a, uint32_t b) {
    constexpr int HI = TB ? 64 : 0x40000040, ST = TB ? 16 : 2;
    wg_fence();
    wss80<TB, !FIRST, HI>(acc, a, b);
    wss80<TB, 1, HI>(acc, a + 128, b + ST);
    wss80<TB, 1, HI>(acc, a + 256, b + 2 * ST);
    wss80<TB, 1, HI>(acc, a + 384, b + 3 * ST);
    wg_commit();
}
template <int I, int N, class F> __device__ __forceinline__ void static_for(F&& f) {
    if constexpr (I < N) { f(std::integral_constant<int, I>{}); static_for<I + 1, N>(f); }
}

__global__ void __launch_bounds__(NTHREADS, 1)
egnn_kernel(const Params P, const __grid_constant__ CUtensorMap tm_h, const __grid_constant__ CUtensorMap tm_we,
            const __grid_constant__ CUtensorMap tm_wh, const __grid_constant__ CUtensorMap tm_b) {
    extern __shared__ __align__(1024) uint8_t smem[];
    constexpr uint32_t sb = 1024;
    if ((uint32_t)__cvta_generic_to_shared(smem) != sb) return;
    const int tid = threadIdx.x, lane = tid & 31, cta = blockIdx.x;
    const int wg = __shfl_sync(~0u, tid >> 7, 0), w = __shfl_sync(~0u, (tid >> 5) & 3, 0), t128 = tid & 127;
    const int g = lane >> 2, q = lane & 3;
    const int n0 = cta * NPC, nvalid = min(NPC, NN - n0);
    TIM(0);

    constexpr int PACE = 2;
    constexpr int NR = EPC / 2;
    const int ne = min(EPC, NE - cta * EPC);
    const uint32_t dum = sb + OFF_DUM + 4 * lane;
    const uint32_t wbase = sb + OFF_W + wg * 8192, mtb = sb + OFF_MT + wg * 10240, mbw = sb + MB_W + wg * 24;
    const uint32_t stm_off = ((lane & 7) + 8 * (lane >> 4)) * 128 + (((2 * w + ((lane >> 3) & 1)) ^ (lane & 7)) << 4);
    uint32_t Cp[20], wf[6] = {0, 0, 0, 0, 0, 0};
    float acc[40];
    auto retire = [&](auto cc) {
        constexpr int c = decltype(cc)::value, n = c < 3 ? c + 4 : c + 3, sl = (n - 1) % 3;
        if constexpr (c >= 9) { arrive_one(sb + MB_V + (c - 9) * 64 + 8); if (c == 11) arrive_one(sb + MB_V + 192 + 8); }
        else if constexpr (c != 3) {
            bar_sync(1 + wg, 128);
            if (w == (c & 3) && elect()) {
                mbar_expect(mbw + 8 * sl, 8192);
                tma2d(wbase + (sl + 1) % 3 * 32768, n < 8 ? &tm_we : &tm_wh, wg * 64, (n & 3) * 64, mbw + 8 * sl);
            }
        }
    };
    auto chunk = [&](auto cc) {
        constexpr int c = decltype(cc)::value, k = c & 3, sl = c < 4 ? c : (c - 1) % 3;
        if (c < 4) mbar_wait(sb + MB_H + 8 * k, 0);
        else mbar_wait(mbw + 8 * sl, ((c - 4) / 3) & 1);
        TIM(16 + c);
        gemm_chunk<0, k == 0>(acc, (sl == 3 ? mtb : wbase + (sl + 1) % 3 * 32768) >> 4, (sb + OFF_H + k * 10240) >> 4);
        if (c == 8) {
            const int col = wg * 64 + w * 16 + g;
            const unsigned short* we = (const unsigned short*)P.w_e + (512 + 2 * q) * DD + col;
            if (q < 3) { wf[0] = __ldg(we); wf[2] = __ldg(we + 8); }
            if (q < 2) { wf[1] = __ldg(we + DD); wf[3] = __ldg(we + DD + 8); }
            wf[4] = __ldg((const unsigned short*)P.w_x + col);
            wf[5] = __ldg((const unsigned short*)P.w_x + col + 8);
        }
        if (k) { wg_wait<1>(); retire(std::integral_constant<int, (c > 0 ? c - 1 : 0)>{}); }
        if (k == 3) {
            wg_wait<0>();
            pin<40>(acc);
            retire(cc);
#pragma unroll
            for (int j = 0; j < 20; j++) Cp[j] = c < 8 ? halve_h2(packh(acc[2 * j], acc[2 * j + 1])) : pack(acc[2 * j], acc[2 * j + 1]);
            pin<20>(Cp);
            if (c == 3) {
                bar_sync(1 + wg, 128);
#pragma unroll
                for (int j = 0; j < 5; j++) stsm4t(mtb + j * 2048 + stm_off, Cp[4 * j], Cp[4 * j + 1], Cp[4 * j + 2], Cp[4 * j + 3]);
                fence_async();
                arrive_one(sb + MB_B);
                TIM(4);
            }
            if (c == 7) {
                mbar_wait(sb + MB_BR, 0);
#pragma unroll
                for (int j = 0; j < 5; j++) stsm4(mtb + j * 2048 + (lane >> 4) * 1024 + (w * 16 + (lane & 15)) * 16, Cp[4 * j], Cp[4 * j + 1], Cp[4 * j + 2], Cp[4 * j + 3]);
                __syncwarp();
            }
        }
    };
    if (tid >= NR) {
        if (elect()) {
#pragma unroll
            for (int i = 0; i < 4; i++) { mbar_init(sb + MB_H + 8 * i, 1); mbar_expect(sb + MB_H + 8 * i, 10240 + 32768); }
            mbar_init(sb + MB_META, NR / 32);
            asm volatile("fence.mbarrier_init.release.cluster;" ::: "memory");
        }
        bar_sync(5, NTHREADS);
        if (elect()) {
#pragma unroll
            for (int i = 0; i < 4; i++) {
                if (i < PACE) tma2d(sb + OFF_H + i * 10240, &tm_h, i * 64, n0, sb + MB_H + 8 * i);
                if (i == 0) l2_prefetch((const char*)P.w_e + min(cta, 128) * 2048, cta < 128 ? 2048 : 2560);
#pragma unroll
                for (int k = 0; k < 4; k++)
                    tma2d(i < 3 ? sb + OFF_W + k * 8192 + (i + 1) % 3 * 32768 : sb + OFF_MT + k * 10240, &tm_we, k * 64, 256 + i * 64, sb + MB_H + 8 * i);
            }
#pragma unroll
            for (int i = PACE; i < 4; i++) {
                mbar_wait(sb + MB_H + 8 * (i - PACE), 0);
                tma2d(sb + OFF_H + i * 10240, &tm_h, i * 64, n0, sb + MB_H + 8 * i);
            }
            mbar_wait(sb + MB_H + 16, 0);
            l2_prefetch(P.ea + cta * EPC, ne * 8);
            l2_prefetch((const char*)P.w_h + (cta & 127) * 2048, 2048);
            TIM(1);
            mbar_wait(sb + MB_B, 0);
            TIM(8);
#pragma unroll
            for (int k = 0; k < 4; k++)
                asm volatile("cp.async.bulk.tensor.2d.global.shared::cta.bulk_group [%0, {%2, %3}], [%1];"
                             ::"l"(&tm_b), "r"(sb + OFF_MT + k * 10240), "r"(k * 64), "r"(n0) : "memory");
            asm volatile("cp.async.bulk.commit_group;\n\tcp.async.bulk.wait_group.read 0;" ::: "memory");
            mbar_arrive(sb + MB_BR);
            asm volatile("cp.async.bulk.wait_group 0;" ::: "memory");
            fence_gpu();
            asm volatile("red.relaxed.gpu.global.add.u32 [%0],1;" ::"l"(P.cnt) : "memory");
        }
        __syncwarp();
    } else {
        if (wg * 4 + w < 13 && elect()) {
            const int i = wg * 4 + w;
            const uint32_t a = i < 9 ? sb + MB_W + 16 * i : sb + MB_V + 64 * (i - 9);
            mbar_init(a, i < 6 || i == 8 ? 1 : i < 8 ? 2 : 66);
            mbar_init(a + 8, i < 6 ? 1 : i < 8 ? 2 : 16);
        }
        int ds[2] = {0, 0}, sr[2] = {0, 0}, own[2], r[2];
#pragma unroll
        for (int i = 0; i < 2; i++)
            if (tid + i * NR < ne) { ds[i] = __ldg(P.dst + cta * EPC + tid + i * NR); sr[i] = __ldg(P.src + cta * EPC + tid + i * NR); }
        uint32_t pv = 0;
        if (tid < 320) { if ((tid & 3) < 3 && (tid >> 2) < nvalid) pv = __ldg((const unsigned short*)P.pos + (n0 + (tid >> 2)) * 3 + (tid & 3)); }
        else if (tid == 320) pv = ld_rlx(P.cnt);
        sts32_gt(sb + OFF_CNT + 4 * tid, 0, 159, tid);
        bar_sync(5, NTHREADS);
        TIM(1);
#pragma unroll
        for (int i = 0; i < 2; i++) { own[i] = ds[i] / NPC; r[i] = atoms_inc(tid + i * NR < ne ? sb + OFF_CNT + 4 * own[i] : dum); }
#pragma unroll
        for (int i = 0; i < 2; i++)
            sts32_gt(sb + OFF_V + own[i] * 256 + 4 * (r[i] + (r[i] * 43 >> 7) + 1), (ds[i] - own[i] * NPC) | ((tid + i * NR) << 7) | (sr[i] << 18),
                     tid + i * NR < ne ? 48 : INT_MIN, r[i]);
        if (tid < 320) asm volatile("st.shared.u16 [%0],%1;" ::"r"(sb + OFF_PD + 2 * tid), "r"(pv) : "memory");
        else if (tid == 320) sts32(sb + OFF_BCNT + 92, pv / NCTA + 1);
        TIM(13);
        bar_sync(5, NR);
        const uint32_t epoch = lds32(sb + OFF_BCNT + 92);
        const int o = tid >> 3, j = tid & 7, o1 = min(o + NR / 8, NCTA - 1);
        const uint32_t c0 = lds32(sb + OFF_CNT + 4 * o), c1 = lds32(sb + OFF_CNT + 4 * o1);
        uint4 p0 = lds128(sb + OFF_V + o * 256 + j * 16), p1 = lds128(sb + OFF_V + o1 * 256 + j * 16);
        p0.x = (epoch << 16) | c0;
        p1.x = (epoch << 16) | c1;
        uint4* g0 = &P.in[(o * NCTA + cta) * 8 + j];
        uint4* g1 = &P.in[(o1 * NCTA + cta) * 8 + j];
        st_pkt(g0, p0);
        if (tid < NCTA * 8 - NR) st_pkt(g1, p1);
        if (max(c0, c1) > 24) {
            uint4 x0 = lds128(sb + OFF_V + o * 256 + 128 + j * 16), x1 = lds128(sb + OFF_V + o1 * 256 + 128 + j * 16);
            x0.x = p0.x;
            x1.x = p1.x;
            st_pkt(g0 + NCTA * NCTA * 8, x0);
            st_pkt(g1 + NCTA * NCTA * 8, x1);
        }
        TIM(2);
        const uint32_t tg = epoch << 16;
        const uint4* inb = &P.in[cta * NCTA * 8];
        if (wg < 4) {
            asm volatile("bar.arrive 8, %0;" ::"n"(NR) : "memory");
            static_for<0, 4>(chunk);
        } else {
            bar_sync(8, NR);
            if (t128 == 0) {
                asm volatile("red.relaxed.gpu.global.add.u32 [%0],1;" ::"l"(P.cnt + 1) : "memory");
                for (int k = 0; k < SPIN; k++) if ((int)(ld_rlx(P.cnt + 1) - epoch * NCTA) >= 0) break;
            }
            if (w) {
                const uint32_t nr = 127 | ((n0 + (lane & 7) * 4) << 18), np = cta * 0x01010101u;
#pragma unroll
                for (int i = 0; i < CAP / 256; i++) sts128(sb + OFF_REC - 128 + 16 * (t128 - 32) + 1024 * i, make_uint4(nr, nr + (1 << 18), nr + (2 << 18), nr + (3 << 18)));
#pragma unroll
                for (int i = 0; i < CAP / 1024; i++) sts128(sb + OFF_PRD - 32 + 16 * (t128 - 32) + 1024 * i, make_uint4(np, np, np, np));
                sts128(sb + OFF_EV + 16 * lane, make_uint4(0, 0, 0, 0));
                if (t128 == 32) { sts32(sb + OFF_PD + 8 * 127, 0); sts32(sb + OFF_PD + 8 * 127 + 4, 0); }
            }
            bar_sync(9, 96);
            TIM(12);
            uint4 pk[11];
            for (int k = 0; k < SPIN; k++) {
                uint32_t bad = 0;
#pragma unroll
                for (int i = 0; i < 11; i++) pk[i] = ld_pkt(inb + t128 + 96 * i);
#pragma unroll
                for (int i = 0; i < 11; i++) bad |= pk[i].x ^ tg;
                if (bad < 65536) break;
            }
#pragma unroll
            for (int i = 0; i < 11; i++) sts128(sb + OFF_V + 16 * (t128 + 96 * i), pk[i]);
            TIM(10);
        }
        bar_sync(5, NR);
        int nt;
        uint4 pk[2] = {lds128(sb + OFF_V + 16 * tid), lds128(sb + OFF_V + 16 * (tid + NR))};
        if (tid >= NCTA * 8 - NR) pk[1].x = 0;
        inb += tid;
        TIM(3);
        int n[2];
#pragma unroll
        for (int i = 0; i < 2; i++) {
            n[i] = (pk[i].x & 0xffff) - 3 * (tid & 7);
            reds_inc(n[i] > 0 ? sb + OFF_BCNT + (pk[i].y & 0x78) : dum);
            reds_inc(n[i] > 1 ? sb + OFF_BCNT + (pk[i].z & 0x78) : dum);
            reds_inc(n[i] > 2 ? sb + OFF_BCNT + (pk[i].w & 0x78) : dum);
        }
        if (max(n[0], n[1]) > 24) {
#pragma unroll 1
            for (int i = 0; i < 2; i++) {
                const int m = (i ? n[1] : n[0]) - 24;
                if (m <= 0) continue;
                uint4 x = ld_pkt(inb + i * NR + NCTA * NCTA * 8);
                for (int k = 0; k < SPIN && (x.x ^ tg) >= 65536; k++) x = ld_pkt(inb + i * NR + NCTA * NCTA * 8);
#pragma unroll 1
                for (int k = 0; k < min(3, m); k++) {
                    const uint32_t r = k == 0 ? x.y : k == 1 ? x.z : x.w, sl = atoms_inc(sb + OFF_BCNT + 80);
                    if ((x.x & 0xffff) > 48 || sl >= XCAP) sts32(sb + OFF_BCNT + 84, 1);
                    else { sts32(sb + OFF_X + 8 * sl, r); sts32(sb + OFF_X + 8 * sl + 4, (tid + i * NR) >> 3); reds_inc(sb + OFF_BCNT + (r & 0x78)); }
                }
            }
        }
        auto bucket_scan = [&]() {
            bar_sync(5, NR);
            if (tid < 32) {
                int c[10];
#pragma unroll
                for (int i = 0; i < 5; i++) { const uint4 x = lds128(sb + OFF_BCNT + 16 * i); c[2 * i] = x.x; c[2 * i + 1] = x.z; }
                int st = 0, lim = 32, nx = 0x7fffffff;
#pragma unroll
                for (int b = 0; b < 9; b++) {
                    st = max(st + c[b], lim);
                    lim = (st | 31) + 65;
                    if (lane == b) nx = st;
                }
                const int mytau = nx >> 5;
                asm volatile("{.reg .pred p; setp.lt.s32 p,%3,10; @p st.shared.v2.u32 [%0],{%1,%2};}"
                             ::"r"(sb + OFF_SP + 8 * tid), "r"(min(mytau - 1, max(st + c[9] + 31, lim - 32) >> 5)), "r"(mytau + 1), "r"(tid) : "memory");
                sts32_gt(sb + OFF_BCNT + 12 + 8 * tid, nx, 9, tid);
            }
            bar_sync(5, NR);
            nt = lds32(sb + OFF_SP + 72);
        };
        TIM(14);
        bucket_scan();
        const uint2 xo = lds64(sb + OFF_BCNT + 80);
        const bool fast = xo.y == 0 && nt <= CAP / 32 - 8;
        TIM(15);
        if (fast) {
            uint32_t ps[6];
#pragma unroll
            for (int i = 0; i < 2; i++) {
                ps[3 * i] = atoms_inc(n[i] > 0 ? sb + OFF_BCNT + 4 + (pk[i].y & 0x78) : dum);
                ps[3 * i + 1] = atoms_inc(n[i] > 1 ? sb + OFF_BCNT + 4 + (pk[i].z & 0x78) : dum);
                ps[3 * i + 2] = atoms_inc(n[i] > 2 ? sb + OFF_BCNT + 4 + (pk[i].w & 0x78) : dum);
            }
#pragma unroll
            for (int i = 0; i < 2; i++) {
                const uint32_t r[3] = {pk[i].y, pk[i].z, pk[i].w};
#pragma unroll
                for (int k = 0; k < 3; k++) {
                    sts32_gt(sb + OFF_REC + 4 * ps[3 * i + k], r[k], n[i], k);
                    sts8_gt(sb + OFF_PRD + ps[3 * i + k], (tid + i * NR) >> 3, n[i], k);
                }
            }
            if (tid < (int)xo.x) {
                const uint2 x = lds64(sb + OFF_X + 8 * tid);
                const uint32_t p = atoms_inc(sb + OFF_BCNT + 4 + (x.x & 0x78));
                sts32(sb + OFF_REC + 4 * p, x.x);
                sts8_gt(sb + OFF_PRD + p, x.y, 1, 0);
            }
        } else {
            bar_sync(5, NR);
            if (tid < 23) sts32(sb + OFF_BCNT + 4 * tid, 0);
            bar_sync(5, NR);
            int below = 0;
#pragma unroll 2
            for (int e = tid; e < NE; e += NR) {
                const int l = __ldg(P.dst + e) - n0;
                below += l < 0;
                if (l >= 0 && l < NPC) reds_inc(sb + OFF_BCNT + (l & 0x78));
            }
            asm volatile("red.shared.add.u32 [%0],%1;" ::"r"(sb + OFF_BCNT + 88), "r"(below) : "memory");
            bucket_scan();
            const int gbase = lds32(sb + OFF_BCNT + 88) + cta * 1280;
            if (tid == 0) sts32(sb + OFF_BCNT + 84, 1);
#pragma unroll 1
            for (int i = tid; i < nt * 32 + 256; i += NR) g_sidx[gbase + i] = 127u << 18;
            bar_sync(5, NR);
#pragma unroll 2
            for (int e = tid; e < NE; e += NR) {
                const int l = __ldg(P.dst + e) - n0;
                if (l >= 0 && l < NPC) g_sidx[gbase + atoms_inc(sb + OFF_BCNT + 4 + (l & 0x78))] = e | (l << 18);
            }
        }
        arrive_one(sb + MB_META);
    }
    TIM(5);

    if (wg == 4) {
        asm volatile("setmaxnreg.dec.sync.aligned.u32 %0;" ::"n"(REG_AUX));
        mbar_wait(sb + MB_META, 0);
        const uint4 st4 = lds128(sb + OFF_BCNT + 80);
        const uint32_t epoch = st4.w;
        const int nt = lds32(sb + OFF_SP + 72), gbase = st4.z + cta * 1280, mytau = lds32(sb + OFF_SP + 8 * min(lane, 9) + 4) - 1;
        const bool fast = st4.y == 0;
        TIM(4);
        auto feed = [&](auto fastc) {
            constexpr bool FAST = decltype(fastc)::value;
            uint32_t rec, s0, s1;
            uint2 ea;
            const uint32_t* posw = (const uint32_t*)P.pos;
            const uint2* eap = P.ea;
            int fp = (w - 1) * 32 + (lane & 7) * 4 + (lane >> 3);
            auto fetch = [&]() {
                uint32_t e;
                if (FAST) { rec = lds32(sb + OFF_REC + 4 * fp); e = lds8(sb + OFF_PRD + fp) * EPC + ((rec >> 7) & 2047); }
                else { const uint32_t x = fp < 0 ? 127u << 18 : g_sidx[gbase + fp]; e = x & 0x3ffff; rec = (x >> 18) | (__ldg(P.src + e) << 18); }
                ea = __ldg(eap + e);
                const uint32_t* pp = posw + ((rec >> 18) * 3 >> 1);
                s0 = __ldg(pp);
                s1 = __ldg(pp + 1);
                fp += 128;
            };
            auto planes = [&](uint32_t va, int stride, uint32_t wi, const uint32_t* vv) {
#pragma unroll
                for (int c = 0; c < 4; c++) sts128(va + c * stride, make_uint4(0, 0, 0, 0));
#pragma unroll
                for (int c = 0; c < 4; c++)
                    asm volatile("{.reg .pred p; setp.lt.u32 p,%2,4; @p st.shared.u32 [%0],%1;}" ::"r"(va + c * stride + 4 * wi), "r"(vv[c]), "r"(wi) : "memory");
            };
            auto build = [&](int p, bool wait) {
                const int u = 2 * p + (w & 1);
                const uint32_t mb = sb + MB_V + ((p & 3) << 6), loc = rec & 127;
                const int b = __popc(__ballot_sync(~0u, mytau < u));
                const bool ev = __any_sync(~0u, mytau + 1 == u);
                const uint2 d = lds64(sb + OFF_PD + 8 * loc);
                const uint32_t sh = (rec >> 14) & 16;
                const uint32_t dxy = hsub2(d.x, __funnelshift_r(s0, s1, sh)), dz = hsub2(d.y, s1 >> sh);
                const uint32_t sq = hmul2(dxy, dxy);
                const uint32_t hxy = packh(bflo(dxy), bfhi(dxy));
                const uint4 f = make_uint4(packh(rbf(bflo(sq) + bfhi(sq) + bflo(hmul2(dz, dz))), bflo(ea.x)), packh(bfhi(ea.x), bflo(ea.y)), packh(bfhi(ea.y), bflo(dz)), 0);
                const uint32_t sl = (loc & 1) << 4;
                const uint32_t vv[4] = {0x3c00u << sl, (hxy & 0xffff) << sl, (hxy >> 16) << sl, (f.z >> 16) << sl};
                if (wait) mbar_wait(sb + MB_V + (((p + 1) & 3) << 6) + 8, (p + 1) >> 2);
                const uint32_t va = sb + OFF_V + (u & 7) * 512 + lane * 16, wi = (loc >> 1) - 4 * b;
                sts128(va, f);
                planes(va + 4096, 4096, wi, vv);
                if (ev) planes(sb + OFF_EV + 512 + ((b - 1) & 3) * 2048 + lane * 16, 512, wi + 4, vv);
                fence_async();
                arrive_one(mb);
            };
            const int ng = (nt + 1) >> 1, par = w >> 1;
            const char* gB = (const char*)P.B + (lane & 7) * 16;
            const uint32_t r = lane >> 3, dst0 = sb + OFF_W + (w & 1) * 4096 + r * 128 + (((lane & 7) ^ r) << 4);
            auto gather = [&](int p, bool wait) {
                const uint32_t mb = sb + MB_V + ((p & 3) << 6);
                uint4 s[2];
#pragma unroll
                for (int hh = 0; hh < 2; hh++) {
                    const int p0 = p * 64 + (w & 1) * 32 + hh * 16 + r * 4;
                    if (FAST) s[hh] = lds128(sb + OFF_REC + 4 * p0);
                    else s[hh] = make_uint4(__ldg(P.src + (g_sidx[gbase + p0] & 0x3ffff)) << 18, __ldg(P.src + (g_sidx[gbase + p0 + 1] & 0x3ffff)) << 18,
                                            __ldg(P.src + (g_sidx[gbase + p0 + 2] & 0x3ffff)) << 18, __ldg(P.src + (g_sidx[gbase + p0 + 3] & 0x3ffff)) << 18);
                }
                if (wait) mbar_wait(mb + 8, 0);
#pragma unroll
                for (int hh = 0; hh < 2; hh++) {
                    const uint32_t dst = (dst0 ^ (hh * 64)) + ((p & 3) << 15);
                    if (hh) { cp_row<512>(dst, gB, s[1].x >> 18); cp_row<1536>(dst, gB, s[1].y >> 18); cp_row<2560>(dst, gB, s[1].z >> 18); cp_row<3584>(dst, gB, s[1].w >> 18); }
                    else { cp_row<0>(dst, gB, s[0].x >> 18); cp_row<1024>(dst, gB, s[0].y >> 18); cp_row<2048>(dst, gB, s[0].z >> 18); cp_row<3072>(dst, gB, s[0].w >> 18); }
                }
                asm volatile("cp.async.mbarrier.arrive.noinc.shared.b64 [%0];" ::"r"(mb) : "memory");
            };
            fetch();
            build(par, false);
            fetch();
            TIM(9);
            if (t128 == 0) for (int k = 0; k < SPIN; k++) if ((int)(ld_acq(P.cnt) - epoch * NCTA) >= 0) break;
            bar_sync(5, 128);
            TIM(11);
            int p = par ^ 1;
#pragma unroll 1
            for (; p < 3; p += 2) gather(p, true);
#pragma unroll 1
            for (; p < ng; p += 2) {
                build(p - 1, true);
                gather(p, false);
                fetch();
            }
            build(p - 1, true);
#pragma unroll 1
            for (; p < ng + 4; p += 2) {
                const uint32_t mb = sb + MB_V + ((p & 3) << 6);
                mbar_wait(mb + 8, (p >> 2) & 1);
                if (elect()) {
                    if (p < ng + 2) asm volatile("mbarrier.arrive.shared.b64 _, [%0], %1;" ::"r"(mb), "r"(32 + p - ng) : "memory");
                    const int c = p - ng;
                    fence_async();
                    mbar_expect(sb + MB_W2 + 8 * c, 16384);
#pragma unroll
                    for (int k = 0; k < 2; k++)
                        tma2d(sb + OFF_W + (2 * (w & 1) + k) * 8192 + ((p & 3) << 15), &tm_wh, (2 * (w & 1) + k) * 64, 256 + 64 * c, sb + MB_W2 + 8 * c);
                }
                __syncwarp();
            }
        };
        if (fast) feed(std::true_type{}); else feed(std::false_type{});
        TIM(6);
        bar_sync(6, NTHREADS);
#pragma unroll 1
        for (int i = t128; i < nvalid * 3; i += 128) {
            const int n = i / 3, d = i - n * 3;
            const float* u = (const float*)P.U + cta * 16 * 240 + (n >> 3) * 24 + d * 8 + (n & 7);
            float s = 0.f;
#pragma unroll
            for (int k = 0; k < 16; k++) s += __ldcg(u + k * 240);
            P.out[NN * DD + n0 * 3 + i] = __float2bfloat16(bflo(lds16(sb + OFF_PD + 8 * n + 2 * d)) + s);
        }
        TIM(7);
        TIMDUMP();
    } else {
        const uint32_t frag = mtb + (w * 16 + g) * 16 + q * 4;
        const uint32_t row_off = (t128 >> 3) * 128 + (((t128 & 7) ^ ((t128 >> 3) & 7)) << 4);
        const int grow = (n0 + (t128 >> 3)) * 32 + wg * 8 + (t128 & 7), rleft = nvalid - (t128 >> 3);
        static_for<4, 12>(chunk);
        asm volatile("setmaxnreg.inc.sync.aligned.u32 %0;" ::"n"(REG_CON));
        uint32_t WA[4] = {packh(0.5f * bflo(wf[0]), 0.5f * bflo(wf[1])), packh(0.5f * bflo(wf[2]), 0.5f * bflo(wf[3])), 0, 0};
        const float wx0 = bflo(wf[4]), wx1 = bflo(wf[5]);
        TIM(6);

        auto init_s = [&](uint32_t* s, uint32_t a) { ldsm4t(s, a); ldsm4t(s + 4, a + 2048); pin<8>(s); };
        uint32_t S0[8], S1[8];
        float T[16] = {};
        uint32_t P0[8], P1[8] = {};
        WA[2] = lds32(frag);
        WA[3] = lds32(frag + 128);
        constexpr uint32_t fd0 = ((sb + OFF_V) >> 4) | (256 << 16), vd0 = ((sb + OFF_V + 4096) >> 4) | (8 << 16), ev0 = (sb + OFF_EV) >> 4;
        uint32_t mptr = frag, sp = 0;
        int nxt = lds32(sb + OFF_SP + sp);
        float2* uptr = P.U + (cta * 16 + wg * 4 + w) * 120 + lane;
        uint32_t u3[3];
        auto flush1 = [&]() {
            sts32(mptr, pack(T[0], T[1]));
            sts32(mptr + 128, pack(T[2], T[3]));
#pragma unroll
            for (int d = 0; d < 3; d++) u3[d] = pack(fmaf(wx1, T[4 * d + 6], wx0 * T[4 * d + 4]), fmaf(wx1, T[4 * d + 7], wx0 * T[4 * d + 5]));
            pin<3>(u3);
            pin<16>(T);
            mptr += 1024;
        };
        auto flush2 = [&]() {
            float c0, c1, c2, c3;
            const uint32_t one = 0x3f803f80u;
            asm volatile("mma.sync.aligned.m16n8k16.row.col.f32.bf16.bf16.f32 {%0,%1,%2,%3},{%4,%5,%6,%5},{%7,%8},{%9,%9,%9,%9};"
                         : "=f"(c0), "=f"(c1), "=f"(c2), "=f"(c3) : "r"(g == 0 ? one : 0u), "r"(0u), "r"(g == 1 ? one : 0u), "r"(movm(u3[0])), "r"(movm(u3[1])), "f"(0.f));
            asm volatile("mma.sync.aligned.m16n8k8.row.col.f32.bf16.bf16.f32 {%0,%1,%2,%3},{%4,%5},{%6},{%0,%1,%2,%3};"
                         : "+f"(c0), "+f"(c1), "+f"(c2), "+f"(c3) : "r"(g == 2 ? one : 0u), "r"(0u), "r"(movm(u3[2])));
            if (g < 3) *uptr = make_float2(c0, c1);
            uptr += 12;
        };
        auto act = [&](uint32_t* s, uint32_t* p, int lo, int hi) {
#pragma unroll
            for (int i = lo; i < hi; i++) p[i] = silu_half_h2(s[i]);
        };
        uint32_t cnt = 64, prev = 0, cur = 64, last;
        int t = 0;
        bool plain, rdy;
        const uint32_t gld = wbase + stm_off;
        auto step = [&](auto kind, auto odd, uint32_t* sc, uint32_t* sn, uint32_t* pn, uint32_t* pp) {
            constexpr int KIND = decltype(kind)::value, ODD = decltype(odd)::value;
            const uint32_t vd = vd0 + 32 * ODD + prev, fd = fd0 + 32 * ODD + cur, ga = gld + 4096 * ODD + (cur << 9);
            const uint32_t evo = 32 + ((sp << 4) & 384);
            uint32_t NA[4];
            if (KIND) { sp += 4; nxt = lds32(sb + OFF_SP + sp); }
            if (KIND == 1) {
                NA[0] = WA[0]; NA[1] = WA[1];
                NA[2] = lds32(mptr + 1024);
                NA[3] = lds32(mptr + 1024 + 128);
                pin<4>(NA);
            }
            wg_fence();
            if (KIND == 2) {
                wrs32<1, 1, 32>(T, pp, ev0 + (8 << 16) + evo);
                wrs32h(sn, WA, fd);
                wrs32<1, 1, 32>(T, pp + 4, ev0 + (8 << 16) + 16 + evo);
            } else {
                if (KIND == 1) wrs32h(sn, NA, fd);
                wrs32<1, 1, 256>(T, pp, vd);
                wrs32h(sn, WA, KIND == 1 ? ev0 + (evo << 16) : fd);
                wrs32<1, 1, 256>(T, pp + 4, vd + 16);
            }
            wg_commit();
            t++;
            plain = t != nxt;
            if (ODD) { cnt += 64; rdy = mbar_try(sb + MB_V + (cnt & 255), cnt >> 8); }
            act(sc, pn, 0, 4);
            if (KIND == 2) {
                pin<4>(pn);
                wg_wait<0>();
                pin<16>(T);
                flush1();
                wg_fence();
                wrs32<1, 0, 256>(T, pp, vd);
                wrs32<1, 1, 256>(T, pp + 4, vd + 16);
                wg_commit();
            }
            act(sc, pn, 4, 8);
            if (KIND == 2) flush2();
            pin<8>(pn);
            init_s(sc, ga);
            wg_wait<0>();
            pin<8>(sn);
            pin<16>(T);
            pin<8>(pp);
            if (KIND == 1) { pin<4>(WA); pin<4>(NA); WA[2] = NA[2]; WA[3] = NA[3]; }
            if (ODD) { arrive_one(sb + MB_V + cur + 8); prev = cur; cur = cnt & 255; }
        };
        using K0 = std::integral_constant<int, 0>;
        using K1 = std::integral_constant<int, 1>;
        using K2 = std::integral_constant<int, 2>;
        mbar_wait(sb + MB_V, 0);
        init_s(S0, gld);
        init_s(S1, gld + 4096);
        pin<4>(WA);
        pin<16>(T);
        pin<8>(P1);
        wg_fence();
        wrs32h(S0, WA, fd0 + 32);
        wg_commit();
        arrive_one(sb + MB_V + 8);
        wg_wait<0>();
        pin<8>(S0);
        plain = nxt != 0;
        rdy = false;
        TIM(8);
        for (;;) {
            if (!rdy) mbar_wait(sb + MB_V + cur, cnt >> 8);
            if (plain) step(K0{}, K0{}, S0, S1, P0, P1);
            else if (sp & 4) step(K2{}, K0{}, S0, S1, P0, P1);
            else if (sp != 72) step(K1{}, K0{}, S0, S1, P0, P1);
            else { last = prev; break; }
            if (plain) step(K0{}, K1{}, S1, S0, P1, P0);
            else if (sp & 4) step(K2{}, K1{}, S1, S0, P1, P0);
            else if (sp != 72) step(K1{}, K1{}, S1, S0, P1, P0);
            else {
#pragma unroll
                for (int i = 0; i < 8; i++) P1[i] = P0[i];
                last = prev + 32;
                break;
            }
        }
        TIM(7);
        pin<8>(P1);
        wg_fence();
        wrs32<1, 1, 256>(T, P1, vd0 + last);
        wrs32<1, 1, 256>(T, P1 + 4, vd0 + last + 16);
        wg_commit();
        wg_wait<0>();
        pin<16>(T);
        flush1();
        fence_async();
        flush2();
        TIM(9);
        bar_sync(6, NTHREADS);
        TIM(10);

#pragma unroll
        for (int j = 0; j < 20; j++) { acc[2 * j] = bflo(Cp[j]); acc[2 * j + 1] = bfhi(Cp[j]); }
        pin<40>(acc);
        uint4 hr[5];
#pragma unroll
        for (int k = 0; k < 4; k++) {
            mbar_wait(sb + MB_W2 + 8 * k, 0);
            gemm_chunk<1, 0>(acc, (wbase + (((((nxt + 1) >> 1) + k) & 3) << 15)) >> 4, ((sb + OFF_MT + k * 10240) >> 4) | (8 << 16));
        }
#pragma unroll
        for (int i = 0; i < 5; i++) if (16 * i < rleft) hr[i] = __ldg(P.h + grow + 512 * i);
        wg_wait<0>();
        pin<40>(acc);
        TIM(11);
        bar_sync(1 + wg, 128);
#pragma unroll
        for (int j = 0; j < 5; j++) {
            uint32_t y[4];
#pragma unroll
            for (int i = 0; i < 4; i++) y[i] = pack(silu_half(0.5f * acc[8 * j + 2 * i]), silu_half(0.5f * acc[8 * j + 2 * i + 1]));
            stsm4t(wbase + (j < 4 ? j * 2048 : 32768) + stm_off, y[0], y[1], y[2], y[3]);
        }
        bar_sync(1 + wg, 128);
#pragma unroll
        for (int i = 0; i < 5; i++) {
            const uint4 y = lds128(wbase + row_off + (i < 4 ? i * 2048 : 32768)), h = hr[i];
            if (16 * i < rleft) ((uint4*)P.out)[grow + 512 * i] = make_uint4(hadd2(h.x, y.x), hadd2(h.y, y.y), hadd2(h.z, y.z), hadd2(h.w, y.w));
        }
        TIM(12);
        TIMDUMP();
    }
}

typedef CUresult (*EncodeFn)(CUtensorMap*, CUtensorMapDataType, cuuint32_t, void*, const cuuint64_t*, const cuuint64_t*,
                             const cuuint32_t*, const cuuint32_t*, CUtensorMapInterleave, CUtensorMapSwizzle,
                             CUtensorMapL2promotion, CUtensorMapFloatOOBfill);

void encode(EncodeFn fn, CUtensorMap* m, const void* p, int rows, int box_rows) {
    cuuint64_t dims[2] = {(cuuint64_t)DD, (cuuint64_t)rows}, strides[1] = {DD * 2};
    cuuint32_t box[2] = {64, (cuuint32_t)box_rows}, es[2] = {1, 1};
    fn(m, CU_TENSOR_MAP_DATA_TYPE_BFLOAT16, 2, const_cast<void*>(p), dims, strides, box, es, CU_TENSOR_MAP_INTERLEAVE_NONE,
       CU_TENSOR_MAP_SWIZZLE_128B, CU_TENSOR_MAP_L2_PROMOTION_L2_128B, CU_TENSOR_MAP_FLOAT_OOB_FILL_NONE);
}

}

extern "C" void kernel_launch(void* const* d_in, const int* in_sizes, int n_in, void* d_out, int out_size) {
    static EncodeFn fn = nullptr;
    static void *pB, *pIn, *pU, *pCnt;
    if (!fn) {
        void* p = nullptr;
        cudaDriverEntryPointQueryResult st;
        cudaGetDriverEntryPoint("cuTensorMapEncodeTiled", &p, cudaEnableDefault, &st);
        fn = (EncodeFn)p;
        cudaGetSymbolAddress(&pB, g_B);
        cudaGetSymbolAddress(&pIn, g_in);
        cudaGetSymbolAddress(&pU, g_U);
        cudaGetSymbolAddress(&pCnt, g_cnt);
        cudaFuncSetAttribute(egnn_kernel, cudaFuncAttributeMaxDynamicSharedMemorySize, SMEM_BYTES + TIMX);
    }
    CUtensorMap tm_h, tm_we, tm_wh, tm_b;
    encode(fn, &tm_b, pB, NN, NPC);
    encode(fn, &tm_h, d_in[0], NN, 80);
    encode(fn, &tm_we, d_in[5], 2 * DD + 5, 64);
    encode(fn, &tm_wh, d_in[7], 2 * DD, 64);
    Params P;
    P.pos = (const __nv_bfloat16*)d_in[1];
    P.ea = (const uint2*)d_in[2];
    P.src = (const int*)d_in[3];
    P.dst = (const int*)d_in[4];
    P.w_e = (const __nv_bfloat16*)d_in[5];
    P.w_x = (const __nv_bfloat16*)d_in[6];
    P.w_h = (const __nv_bfloat16*)d_in[7];
    P.out = (__nv_bfloat16*)d_out;
    P.h = (const uint4*)d_in[0];
    P.cnt = (uint32_t*)pCnt;
    P.in = (uint4*)pIn;
    P.B = (const uint4*)pB;
    P.U = (float2*)pU;
    egnn_kernel<<<NCTA, NTHREADS, SMEM_BYTES + TIMX, cudaStreamPerThread>>>(P, tm_h, tm_we, tm_wh, tm_b);
}
```

```cpp
#include <cuda_runtime.h>
#include <cuda_bf16.h>
#include <cuda.h>
#include <stdint.h>
#include <type_traits>
#include <climits>

namespace {

constexpr int NN = 10000, NE = 160000, DD = 256;
constexpr int NCTA = 132, NPC = 76, EPC = 1216;
constexpr int NTHREADS = 640;
constexpr int REG_CON = 104, REG_AUX = 64;
#define NSG 1
#define NS2 0
#define LATED 0
#define NPB 1
#define NPH 1
#define PSL 120
#define KA 6
constexpr int RC = 200, CAP = 2304;

constexpr int OFF_W = 0;
constexpr int OFF_H = 3 * 32768;
constexpr int OFF_MT = OFF_H + 40960;
constexpr int OFF_V = OFF_MT + 40960;
constexpr int OFF_PL = OFF_V + 3072;
constexpr int OFF_EV = OFF_PL + 5 * 4096;
constexpr int OFF_REC = OFF_V + 32768;
constexpr int OFF_PRD = OFF_REC + CAP * 4;
constexpr int OFF_PD = OFF_PRD + CAP;
constexpr int OFF_WX = OFF_PD + 768;
constexpr int MB_V = OFF_WX + 3072;
constexpr int MB_H = MB_V + 256;
constexpr int MB_W = MB_H + 32;
constexpr int MB_W2 = MB_W + 96;
constexpr int MB_BR = MB_W2 + 32;
constexpr int MB_G0 = MB_BR + 8;
constexpr int MB_B = MB_G0 + 8;
constexpr int MB_META = MB_B + 32;
constexpr int MB_WL = MB_META + 8;
constexpr int MB_VF = MB_WL + 8;
constexpr int MB_GI = MB_VF + 8;
constexpr int MB_W8 = MB_GI + 8;
constexpr int MB_HINT = MB_W8 + 8;
constexpr int OFF_ONE = MB_HINT + 8;
constexpr int OFF_OK = OFF_ONE + 16;
constexpr int OFF_CNT = OFF_OK + 32;
constexpr int OFF_BCNT = OFF_CNT + 544;
constexpr int OFF_SP = OFF_BCNT + 96;
constexpr int OFF_DUM = OFF_SP + 96;
constexpr int SMEM_BYTES = OFF_DUM + 128;
static_assert(SMEM_BYTES <= 232448, "smem");
static_assert((1024 + OFF_PL) % 4096 == 0 && MB_V % 256 == 0 && OFF_EV + 8704 <= OFF_REC && OFF_BCNT % 16 == 0 && OFF_V + NCTA * 256 <= OFF_PD, "layout");

__device__ uint4 g_B[NN * 32];
__device__ uint4 g_in[2][NCTA * NCTA * 8];
__device__ float4 g_U[NCTA * 16 * 80];
__device__ __align__(128) uint32_t g_cnt[8];
__device__ uint32_t g_sidx[NE + NCTA * 1280];
#define TIM(i)
#define TIMDUMP()
#define TIMX 0

__device__ __forceinline__ void mbar_init(uint32_t a, uint32_t n) { asm volatile("mbarrier.init.shared.b64 [%0], %1;" ::"r"(a), "r"(n) : "memory"); }
__device__ __forceinline__ void mbar_expect(uint32_t a, uint32_t bytes) { asm volatile("mbarrier.arrive.expect_tx.shared.b64 _, [%0], %1;" ::"r"(a), "r"(bytes) : "memory"); }
__device__ __forceinline__ void mbar_arrive(uint32_t a) { asm volatile("mbarrier.arrive.shared.b64 _, [%0];" ::"r"(a) : "memory"); }
__device__ __forceinline__ bool mbar_try(uint32_t a, uint32_t par) {
    uint32_t ok;
    asm volatile("{.reg .pred p; mbarrier.try_wait.parity.shared.b64 p, [%1], %2; selp.u32 %0,1,0,p;}" : "=r"(ok) : "r"(a), "r"(par) : "memory");
    return ok;
}
constexpr int SPIN = 1 << 20;
__device__ __forceinline__ void mbar_wait(uint32_t a, uint32_t par) {
    if (mbar_try(a, par)) return;
#pragma unroll 1
    for (int i = 0; i < SPIN; i++) if (mbar_try(a, par)) return;
}
__device__ __forceinline__ void bar_sync(int id, int n) { asm volatile("bar.sync %0, %1;" ::"r"(id), "r"(n) : "memory"); }
__device__ __forceinline__ void keep_alive(uint32_t& z) {
    asm volatile("{.reg .b32 d; mma.sync.aligned.m16n8k8.row.col.f16.f16.f16.f16 {%0,d},{%0,%0},{%0},{%0,%0};}" : "+r"(z));
}
__device__ __forceinline__ void mbar_wait_ka(uint32_t a, uint32_t par, uint32_t& z) {
#pragma unroll 1
    for (int i = 0; i < SPIN; i++) {
        uint32_t ok;
        asm volatile("{.reg .pred p; mbarrier.try_wait.parity.shared.b64 p, [%1], %2, 150; selp.u32 %0,1,0,p;}" : "=r"(ok) : "r"(a), "r"(par) : "memory");
        if (ok) return;
        keep_alive(z);
    }
}
__device__ __forceinline__ bool bar_or(int id, bool v) {
    uint32_t r;
    asm volatile("{.reg .pred p, o; setp.ne.u32 p,%2,0; bar.red.or.pred o, %1, 640, p; selp.u32 %0,1,0,o;}" : "=r"(r) : "r"(id), "r"((uint32_t)v) : "memory");
    return r;
}
__device__ __forceinline__ void fence_async() { asm volatile("fence.proxy.async.shared::cta;" ::: "memory"); }
__device__ __forceinline__ void tma2d(uint32_t dst, const CUtensorMap* m, int x, int y, uint32_t bar) {
    asm volatile("cp.async.bulk.tensor.2d.shared::cluster.global.mbarrier::complete_tx::bytes [%0], [%1, {%3, %4}], [%2];"
                 ::"r"(dst), "l"(m), "r"(bar), "r"(x), "r"(y) : "memory");
}
__device__ __forceinline__ void cp16(uint32_t dst, const void* src) { asm volatile("cp.async.cg.shared.global [%0], [%1], 16;" ::"r"(dst), "l"(src) : "memory"); }
__device__ __forceinline__ void cp_commit() { asm volatile("cp.async.commit_group;" ::: "memory"); }
template <int N> __device__ __forceinline__ void cp_wait() { asm volatile("cp.async.wait_group %0;" ::"n"(N) : "memory"); }
__device__ __forceinline__ uint32_t lds32(uint32_t a) { uint32_t v; asm volatile("ld.shared.u32 %0,[%1];" : "=r"(v) : "r"(a) : "memory"); return v; }
__device__ __forceinline__ uint32_t lds16(uint32_t a) { uint32_t v; asm volatile("ld.shared.u16 %0,[%1];" : "=r"(v) : "r"(a) : "memory"); return v; }
__device__ __forceinline__ uint4 lds128(uint32_t a) { uint4 v; asm volatile("ld.shared.v4.u32 {%0,%1,%2,%3},[%4];" : "=r"(v.x), "=r"(v.y), "=r"(v.z), "=r"(v.w) : "r"(a) : "memory"); return v; }
__device__ __forceinline__ void sts32(uint32_t a, uint32_t v) { asm volatile("st.shared.u32 [%0],%1;" ::"r"(a), "r"(v) : "memory"); }
__device__ __forceinline__ void sts128(uint32_t a, uint4 v) { asm volatile("st.shared.v4.u32 [%0],{%1,%2,%3,%4};" ::"r"(a), "r"(v.x), "r"(v.y), "r"(v.z), "r"(v.w) : "memory"); }
__device__ __forceinline__ uint32_t atoms_inc(uint32_t a) { uint32_t v; asm volatile("atom.shared.add.u32 %0,[%1],1;" : "=r"(v) : "r"(a) : "memory"); return v; }
__device__ __forceinline__ uint32_t ld_acq(const uint32_t* p) { uint32_t v; asm volatile("ld.acquire.gpu.global.u32 %0,[%1];" : "=r"(v) : "l"(p) : "memory"); return v; }
__device__ __forceinline__ uint32_t ld_rlx(const uint32_t* p) { uint32_t v; asm volatile("ld.relaxed.gpu.global.u32 %0,[%1];" : "=r"(v) : "l"(p) : "memory"); return v; }
template <int NP> __device__ __forceinline__ void poll(const uint32_t* p, uint32_t target) {
    uint32_t v[NP];
#pragma unroll
    for (int i = 0; i < NP; i++) { v[i] = ld_rlx(p); if (i + 1 < NP) __nanosleep(PSL); }
#pragma unroll 1
    for (int k = 0; k < SPIN; k++) {
#pragma unroll
        for (int i = 0; i < NP; i++) { if ((int)(v[i] - target) >= 0) return; v[i] = ld_rlx(p); }
    }
}
__device__ __forceinline__ void reds_inc(uint32_t a) { asm volatile("red.shared.add.u32 [%0],1;" ::"r"(a) : "memory"); }
__device__ __forceinline__ uint4 ld_pkt(const uint4* p) {
    uint4 v;
    asm volatile("{.reg .b128 t; ld.relaxed.gpu.global.b128 t,[%4]; mov.b128 {%0,%1,%2,%3},t;}" : "=r"(v.x), "=r"(v.y), "=r"(v.z), "=r"(v.w) : "l"(p) : "memory");
    return v;
}
__device__ __forceinline__ void st_pkt(uint4* p, uint4 v) {
    asm volatile("{.reg .b128 t; mov.b128 t,{%1,%2,%3,%4}; st.relaxed.gpu.global.b128 [%0],t;}" ::"l"(p), "r"(v.x), "r"(v.y), "r"(v.z), "r"(v.w) : "memory");
}
__device__ __forceinline__ void sts32_gt(uint32_t a, uint32_t v, int n, int k) { asm volatile("{.reg .pred p; setp.gt.s32 p,%2,%3; @p st.shared.u32 [%0],%1;}" ::"r"(a), "r"(v), "r"(n), "r"(k) : "memory"); }
__device__ __forceinline__ void sts8_gt(uint32_t a, uint32_t v, int n, int k) { asm volatile("{.reg .pred p; setp.gt.s32 p,%2,%3; @p st.shared.u8 [%0],%1;}" ::"r"(a), "r"(v), "r"(n), "r"(k) : "memory"); }
__device__ __forceinline__ uint4 ldg128_gt(const uint4* p, int n, int k) {
    uint4 v;
    asm volatile("{.reg .pred p; setp.gt.s32 p,%5,%6; @p ld.global.L1::no_allocate.v4.u32 {%0,%1,%2,%3},[%4];}" : "=r"(v.x), "=r"(v.y), "=r"(v.z), "=r"(v.w) : "l"(p), "r"(n), "r"(k) : "memory");
    return v;
}
__device__ __forceinline__ void sts16(uint32_t a, uint32_t v) { asm volatile("st.shared.u16 [%0],%1;" ::"r"(a), "r"(v) : "memory"); }
__device__ __forceinline__ uint32_t lds8(uint32_t a) { uint32_t v; asm volatile("ld.shared.u8 %0,[%1];" : "=r"(v) : "r"(a) : "memory"); return v; }
__device__ __forceinline__ uint2 lds64(uint32_t a) { uint2 v; asm volatile("ld.shared.v2.u32 {%0,%1},[%2];" : "=r"(v.x), "=r"(v.y) : "r"(a) : "memory"); return v; }
__device__ __forceinline__ bool elect() { uint32_t p; asm volatile("{.reg .pred p; elect.sync _|p, 0xffffffff; selp.u32 %0,1,0,p;}" : "=r"(p)); return p; }
__device__ __forceinline__ void arrive_one(uint32_t a) { __syncwarp(); asm volatile("{.reg .pred p; elect.sync _|p, 0xffffffff; @p mbarrier.arrive.shared.b64 _, [%0];}" ::"r"(a) : "memory"); }
template <int DO, int NS> __device__ __forceinline__ void cp_row(uint32_t& dst, const void* base, uint32_t row) {
    uint64_t a;
    asm volatile("mad.wide.u32 %0,%2,512,%1;" : "=l"(a) : "l"(base), "r"(row));
    auto pace = [&](bool on) { if (on) { uint32_t t; asm volatile("mov.u32 %0,%%clock;" : "=r"(t) :: "memory"); dst |= t & (gridDim.x - NCTA); } };
    asm volatile("cp.async.cg.shared.global [%0+%2], [%1], 16;" ::"r"(dst), "l"(a), "n"(DO) : "memory");
    pace(NS >= 3);
    asm volatile("cp.async.cg.shared.global [%0+%2], [%1+128], 16;" ::"r"(dst), "l"(a), "n"(DO + 8192) : "memory");
    pace(NS >= 2);
    asm volatile("cp.async.cg.shared.global [%0+%2], [%1+256], 16;" ::"r"(dst), "l"(a), "n"(DO + 16384) : "memory");
    pace(NS >= 3);
    asm volatile("cp.async.cg.shared.global [%0+%2], [%1+384], 16;" ::"r"(dst), "l"(a), "n"(DO + 24576) : "memory");
    pace(NS >= 1);
}
__device__ __forceinline__ void l2_prefetch(const void* p, uint32_t bytes) { asm volatile("cp.async.bulk.prefetch.L2.global [%0], %1;" ::"l"(p), "r"(bytes) : "memory"); }
__device__ __forceinline__ void fence_gpu() { asm volatile("fence.acq_rel.gpu;" ::: "memory"); }
__device__ __forceinline__ void ldsm4t(uint32_t* r, uint32_t a) {
    asm volatile("ldmatrix.sync.aligned.m8n8.x4.trans.shared.b16 {%0,%1,%2,%3},[%4];" : "=r"(r[0]), "=r"(r[1]), "=r"(r[2]), "=r"(r[3]) : "r"(a) : "memory");
}
__device__ __forceinline__ void stsm4t(uint32_t a, uint32_t r0, uint32_t r1, uint32_t r2, uint32_t r3) {
    asm volatile("stmatrix.sync.aligned.m8n8.x4.trans.shared.b16 [%0],{%1,%2,%3,%4};" ::"r"(a), "r"(r0), "r"(r1), "r"(r2), "r"(r3) : "memory");
}
__device__ __forceinline__ void stsm4(uint32_t a, uint32_t r0, uint32_t r1, uint32_t r2, uint32_t r3) {
    asm volatile("stmatrix.sync.aligned.m8n8.x4.shared.b16 [%0],{%1,%2,%3,%4};" ::"r"(a), "r"(r0), "r"(r1), "r"(r2), "r"(r3) : "memory");
}
__device__ __forceinline__ uint32_t movm(uint32_t x) { uint32_t y; asm volatile("movmatrix.sync.aligned.m8n8.trans.b16 %0,%1;" : "=r"(y) : "r"(x)); return y; }
__device__ __forceinline__ uint32_t pack(float lo, float hi) { uint32_t r; asm("cvt.rn.bf16x2.f32 %0,%1,%2;" : "=r"(r) : "f"(hi), "f"(lo)); return r; }
__device__ __forceinline__ uint32_t packh(float lo, float hi) { uint32_t r; asm("cvt.rn.f16x2.f32 %0,%1,%2;" : "=r"(r) : "f"(hi), "f"(lo)); return r; }
__device__ __forceinline__ uint32_t halve_h2(uint32_t a) { uint32_t r; asm("mul.rn.f16x2 %0,%1,%2;" : "=r"(r) : "r"(a), "r"(0x38003800u)); return r; }
__device__ __forceinline__ uint32_t tanh_h2(uint32_t x) { uint32_t t; asm("tanh.approx.f16x2 %0,%1;" : "=r"(t) : "r"(x)); return t; }
__device__ __forceinline__ uint32_t fma_h2(uint32_t x, uint32_t t) { uint32_t r; asm("fma.rn.f16x2 %0,%1,%2,%1;" : "=r"(r) : "r"(x), "r"(t)); return r; }
__device__ __forceinline__ uint32_t silu_half_h2(uint32_t x) { uint32_t t, r; asm("tanh.approx.f16x2 %0,%1;" : "=r"(t) : "r"(x)); asm("fma.rn.f16x2 %0,%1,%2,%1;" : "=r"(r) : "r"(x), "r"(t)); return r; }
__device__ __forceinline__ float bflo(uint32_t v) { return __uint_as_float(v << 16); }
__device__ __forceinline__ float bfhi(uint32_t v) { return __uint_as_float(v & 0xffff0000u); }
__device__ __forceinline__ float rbf(float x) { return bflo(pack(x, 0.f)); }
__device__ __forceinline__ float silu_half(float x) { float t; asm("tanh.approx.f32 %0,%1;" : "=f"(t) : "f"(x)); return fmaf(x, t, x); }
__device__ __forceinline__ uint32_t hmul2(uint32_t a, uint32_t b) { uint32_t r; asm("mul.rn.bf16x2 %0,%1,%2;" : "=r"(r) : "r"(a), "r"(b)); return r; }
__device__ __forceinline__ uint32_t hsub2(uint32_t a, uint32_t b) { uint32_t r; asm("sub.rn.bf16x2 %0,%1,%2;" : "=r"(r) : "r"(a), "r"(b)); return r; }
__device__ __forceinline__ uint32_t hadd2(uint32_t a, uint32_t b) { uint32_t r; asm("add.rn.bf16x2 %0,%1,%2;" : "=r"(r) : "r"(a), "r"(b)); return r; }

__device__ __forceinline__ void wg_fence() { asm volatile("wgmma.fence.sync.aligned;" ::: "memory"); }
__device__ __forceinline__ void wg_commit() { asm volatile("wgmma.commit_group.sync.aligned;" ::: "memory"); }
template <int N> __device__ __forceinline__ void wg_wait() { asm volatile("wgmma.wait_group.sync.aligned %0;" ::"n"(N) : "memory"); }
template <int N> __device__ __forceinline__ void pin(float* r) {
#pragma unroll
    for (int i = 0; i < N; i++) asm volatile("" : "+f"(r[i])::"memory");
}
template <int N> __device__ __forceinline__ void pin(uint32_t* r) {
#pragma unroll
    for (int i = 0; i < N; i++) asm volatile("" : "+r"(r[i])::"memory");
}
#define D4(o) "+f"(d[o]), "+f"(d[o + 1]), "+f"(d[o + 2]), "+f"(d[o + 3])
template <int TB, int ACC, int BHI> __device__ __forceinline__ void wss80(float* d, uint32_t a, uint32_t b) {
    asm volatile("{.reg .b64 da, db; mov.b64 da,{%40,0x40000040}; mov.b64 db,{%41,%44}; wgmma.mma_async.sync.aligned.m64n80k16.f32.bf16.bf16 "
                 "{%0,%1,%2,%3,%4,%5,%6,%7,%8,%9,%10,%11,%12,%13,%14,%15,%16,%17,%18,%19,%20,%21,%22,%23,%24,%25,%26,%27,%28,%29,%30,%31,%32,%33,%34,%35,%36,%37,%38,%39},"
                 "da,db,%42,1,1,1,%43;}"
                 : D4(0), D4(4), D4(8), D4(12), D4(16), D4(20), D4(24), D4(28), D4(32), D4(36)
                 : "r"(a), "r"(b), "n"(ACC), "n"(TB), "n"(BHI));
}
template <int ACC> __device__ __forceinline__ void wrs32(float* d, const uint32_t* a, uint64_t b) {
    asm volatile("wgmma.mma_async.sync.aligned.m64n32k16.f32.f16.f16 "
                 "{%0,%1,%2,%3,%4,%5,%6,%7,%8,%9,%10,%11,%12,%13,%14,%15},{%16,%17,%18,%19},%20,%21,1,1,1;"
                 : D4(0), D4(4), D4(8), D4(12)
                 : "r"(a[0]), "r"(a[1]), "r"(a[2]), "r"(a[3]), "l"(b), "n"(ACC));
}
__device__ __forceinline__ void wrs32h(uint32_t* d, const uint32_t* a, uint64_t b) {
    asm volatile("wgmma.mma_async.sync.aligned.m64n32k16.f16.f16.f16 {%0,%1,%2,%3,%4,%5,%6,%7},{%8,%9,%10,%11},%12,1,1,1,0;"
                 : "+r"(d[0]), "+r"(d[1]), "+r"(d[2]), "+r"(d[3]), "+r"(d[4]), "+r"(d[5]), "+r"(d[6]), "+r"(d[7])
                 : "r"(a[0]), "r"(a[1]), "r"(a[2]), "r"(a[3]), "l"(b));
}
#undef D4

struct Params {
    const int* dst; const int* src; const __nv_bfloat16* pos; uint32_t* cnt; uint4* in; const uint2* ea;
    const __nv_bfloat16* w_e; const __nv_bfloat16* w_x; const __nv_bfloat16* w_h; __nv_bfloat16* out; const uint4* h; const uint4* B; float4* U;
};

template <int TB, int FIRST> __device__ __forceinline__ void gemm_chunk(float* acc, uint32_t a, uint32_t b) {
    constexpr int HI = TB ? 64 : 0x40000040, ST = TB ? 16 : 2;
    wg_fence();
    wss80<TB, !FIRST, HI>(acc, a, b);
    wss80<TB, 1, HI>(acc, a + 128, b + ST);
    wss80<TB, 1, HI>(acc, a + 256, b + 2 * ST);
    wss80<TB, 1, HI>(acc, a + 384, b + 3 * ST);
    wg_commit();
}
template <int I, int N, class F> __device__ __forceinline__ void static_for(F&& f) {
    if constexpr (I < N) { f(std::integral_constant<int, I>{}); static_for<I + 1, N>(f); }
}

__device__ __forceinline__ void fallback(const Params& P, uint8_t* smem, int n0, int nvalid) {
    const int tid = threadIdx.x, c = tid & 255, half = tid >> 8;
    float* accM = (float*)smem;
    float* accP = accM + NPC * DD;
    float* x = accP + NPC * 4 + half * 4 * 520;
    int* list = (int*)(accP + NPC * 4 + 8 * 520);
    const __nv_bfloat16* h = (const __nv_bfloat16*)P.h;
    auto f = [](const __nv_bfloat16* p, int i) { return __bfloat162float(p[i]); };
    auto silu = [](float z) { z = rbf(z); return rbf(z / (1.f + expf(-z))); };
    auto matvec = [&](const __nv_bfloat16* W, int K, float* z) {
#pragma unroll 2
        for (int k = 0; k < K; k++) {
            const float wv = f(W, k * DD + c);
#pragma unroll
            for (int j = 0; j < 4; j++) z[j] = fmaf(x[j * 520 + k], wv, z[j]);
        }
    };
#pragma unroll 1
    for (int i = tid; i < NPC * (DD + 4); i += 512) accM[i] = 0.f;
#pragma unroll 1
    for (int e0 = 0; e0 < NE; e0 += 512) {
        if (tid == 0) list[512] = 0;
        bar_sync(8, 512);
        if (e0 + tid < NE && (unsigned)(P.dst[e0 + tid] - n0) < (unsigned)nvalid) list[atomicAdd(list + 512, 1)] = e0 + tid;
        bar_sync(8, 512);
        const int cnt = list[512];
#pragma unroll 1
        for (int i0 = 0; i0 < cnt; i0 += 8) {
#pragma unroll 1
            for (int j = 0; j < 4; j++) {
                const int e = list[min(i0 + half * 4 + j, cnt - 1)], d = P.dst[e], s = P.src[e];
                x[j * 520 + c] = f(h, d * DD + c);
                x[j * 520 + DD + c] = f(h, s * DD + c);
                if (c < 4) x[j * 520 + 513 + c] = f((const __nv_bfloat16*)P.ea, e * 4 + c);
                if (c == 4) {
                    float d2 = 0.f;
                    for (int k = 0; k < 3; k++) { const float v = rbf(f(P.pos, d * 3 + k) - f(P.pos, s * 3 + k)); x[j * 520 + 517 + k] = v; d2 += rbf(v * v); }
                    x[j * 520 + 512] = rbf(d2);
                }
            }
            bar_sync(8, 512);
            float z[4] = {0.f, 0.f, 0.f, 0.f};
            matvec(P.w_e, 517, z);
#pragma unroll
            for (int j = 0; j < 4; j++)
                if (i0 + half * 4 + j < cnt) {
                    const int l = P.dst[list[i0 + half * 4 + j]] - n0;
                    const float m = silu(z[j]);
                    atomicAdd(accM + l * DD + c, m);
                    float p = m * f(P.w_x, c);
#pragma unroll
                    for (int o = 16; o; o >>= 1) p += __shfl_xor_sync(~0u, p, o);
                    if ((c & 31) < 3) atomicAdd(accP + l * 4 + (c & 31), p * x[j * 520 + 517 + (c & 31)]);
                }
            bar_sync(8, 512);
        }
    }
#pragma unroll 1
    for (int i0 = 0; i0 < nvalid; i0 += 8) {
        bar_sync(8, 512);
#pragma unroll 1
        for (int j = 0; j < 4; j++) {
            const int n = min(i0 + half * 4 + j, nvalid - 1);
            x[j * 520 + c] = f(h, (n0 + n) * DD + c);
            x[j * 520 + DD + c] = rbf(accM[n * DD + c]);
        }
        bar_sync(8, 512);
        float z[4] = {0.f, 0.f, 0.f, 0.f};
        matvec(P.w_h, 512, z);
#pragma unroll
        for (int j = 0; j < 4; j++)
            if (i0 + half * 4 + j < nvalid) P.out[(n0 + i0 + half * 4 + j) * DD + c] = __float2bfloat16(x[j * 520 + c] + silu(z[j]));
    }
    if (tid < nvalid * 3) P.out[NN * DD + n0 * 3 + tid] = __float2bfloat16(f(P.pos, n0 * 3 + tid) + accP[tid / 3 * 4 + tid % 3]);
}

__global__ void __launch_bounds__(NTHREADS, 1)
egnn_kernel(const Params P, const __grid_constant__ CUtensorMap tm_h, const __grid_constant__ CUtensorMap tm_we,
            const __grid_constant__ CUtensorMap tm_wh, const __grid_constant__ CUtensorMap tm_b) {
    extern __shared__ __align__(1024) uint8_t smem[];
    constexpr uint32_t sb = 1024;
    if ((uint32_t)__cvta_generic_to_shared(smem) != sb) return;
    const int tid = threadIdx.x, lane = tid & 31, cta = blockIdx.x;
    const int wg = __shfl_sync(~0u, tid >> 7, 0), w = __shfl_sync(~0u, (tid >> 5) & 3, 0), t128 = tid & 127;
    const int g = lane >> 2, q = lane & 3;
    const int n0 = cta * NPC, nvalid = min(NPC, NN - n0);
    TIM(0);

#define TRED 1
#define EARLY 3
#define PACE 3
    constexpr int NR = EPC / 2;
    const int ne = min(EPC, NE - cta * EPC);
    const uint32_t dum = sb + OFF_DUM + 4 * lane;
    const uint32_t wbase = sb + OFF_W + wg * 8192, mtb = sb + OFF_MT + wg * 10240, mbw = sb + MB_W + wg * 24;
    const uint32_t stm_off = ((lane & 7) + 8 * (lane >> 4)) * 128 + (((2 * w + ((lane >> 3) & 1)) ^ (lane & 7)) << 4);
    uint32_t Cp[20];
    float acc[40];
    uint32_t kz = 0, a0, a1;
    auto mbv = [&](int p) { return sb + MB_V + (((p + 3) & 3) << 6); };
    constexpr int WBUF[12] = {2, 0, 1, 3, 2, 0, 1, 4, 3, 2, 4, 3}, WBAR[12] = {0, 0, 0, 0, 2, 0, 1, 0, 0, 2, 0, 1}, WNEXT[12] = {4, 5, 6, 0, 9, 0, 0, 10, 11, 0, 0, 0};
    auto waddr = [&](int b) { return b == 3 ? mtb : b == 4 ? sb + OFF_V + wg * 8192 : wbase + b * 32768; };
    auto retire = [&](auto cc) {
        constexpr int c = decltype(cc)::value, n = WNEXT[c];
        if constexpr (!n && c != 3) arrive_one(c == 10 ? sb + MB_VF : mbv(WBUF[c]) + 8);
        if constexpr (n || c == 3 || c == 11) bar_sync(1 + wg, 128);
        if (c == 4 && w == 1 && elect()) {
            mbar_wait(sb + MB_BR, 0);
            mbar_expect(sb + MB_W8, 8192);
            tma2d(mtb, &tm_wh, wg * 64, 0, sb + MB_W8);
        }
        if (n && w == (c & 3) && elect()) {
            mbar_expect(mbw + 8 * WBAR[n], 8192);
            tma2d(waddr(WBUF[n]), n < 8 ? &tm_we : &tm_wh, wg * 64, (n & 3) * 64, mbw + 8 * WBAR[n]);
        }
    };
    auto chunk = [&](auto cc) {
        constexpr int c = decltype(cc)::value, k = c & 3;
        if (c < 4) { if (KA & 1) mbar_wait_ka(sb + MB_H + 8 * k, 0, kz); else mbar_wait(sb + MB_H + 8 * k, 0); }
        else if (c == 7 || c == 8) mbar_wait(sb + (c == 7 ? MB_WL : MB_W8), 0);
        else mbar_wait(mbw + 8 * WBAR[c], c > 8);
        TIM(16 + c);
        gemm_chunk<0, k == 0>(acc, waddr(WBUF[c]) >> 4, (sb + OFF_H + k * 10240) >> 4);
        if (k && (c < 4 || c >= 4 + EARLY)) { wg_wait<1>(); retire(std::integral_constant<int, (c > 0 ? c - 1 : 0)>{}); }
        if (k == 3) {
            wg_wait<0>();
            pin<40>(acc);
            retire(cc);
            if (c == 11) {
#pragma unroll
                for (int j = 0; j < 5; j++) stsm4(mtb + j * 2048 + (lane >> 4) * 1024 + (w * 16 + (lane & 15)) * 16, Cp[4 * j], Cp[4 * j + 1], Cp[4 * j + 2], Cp[4 * j + 3]);
                uint32_t any = 0;
#pragma unroll
                for (int j = 0; j < 20; j += 4) any |= Cp[j] | Cp[j + 2];
                sts32_gt(sb + OFF_OK + 20, 1, any & 0x70007000, 0);
                a0 = Cp[0];
                a1 = Cp[1];
                __syncwarp();
            }
#pragma unroll
            for (int j = 0; j < 20; j++)
                Cp[j] = c == 3 ? halve_h2(packh(acc[2 * j], acc[2 * j + 1])) : c == 7 ? packh(acc[2 * j], acc[2 * j + 1]) : hmul2(pack(acc[2 * j], acc[2 * j + 1]), 0x3f003f00u);
            pin<20>(Cp);
            if (c == 3) {
#pragma unroll
                for (int j = 0; j < 5; j++) stsm4t(mtb + j * 2048 + stm_off, Cp[4 * j], Cp[4 * j + 1], Cp[4 * j + 2], Cp[4 * j + 3]);
                fence_async();
                arrive_one(sb + MB_B + 8 * wg);
                if (KA & 2) keep_alive(kz);
                TIM(4);
            }
        }
    };
    if (tid >= NR) {
        if (elect()) {
#pragma unroll
            for (int i = 0; i < 4; i++) { mbar_init(sb + MB_H + 8 * i, 1); mbar_expect(sb + MB_H + 8 * i, 10240 + 32768 + (i == 3 ? 3072 : 0)); }
            mbar_init(sb + MB_META, NR / 32);
            mbar_init(sb + MB_WL, 1);
            mbar_init(sb + MB_VF, 16);
            mbar_init(sb + MB_GI, 1);
            mbar_init(sb + MB_W8, 4);
            mbar_init(sb + MB_HINT, 3);
            sts128(sb + OFF_ONE, make_uint4(1, 0, 0, 0));
            fence_async();
            asm volatile("fence.mbarrier_init.release.cluster;" ::: "memory");
        }
        bar_sync(5, NTHREADS);
        if (elect()) {
#pragma unroll
            for (int i = 0; i < 4; i++) {
                if (i < PACE) tma2d(sb + OFF_H + i * 10240, &tm_h, i * 64, n0, sb + MB_H + 8 * i);
                if (i == 0) l2_prefetch((const char*)P.w_e + (cta & 127) * 2048, 2048);
#pragma unroll
                for (int k = 0; k < 4; k++)
                    tma2d(i < 3 ? sb + OFF_W + k * 8192 + WBUF[i] * 32768 : sb + OFF_MT + k * 10240, &tm_we, k * 64, 256 + i * 64, sb + MB_H + 8 * i);
            }
            asm volatile("cp.async.bulk.shared::cluster.global.mbarrier::complete_tx::bytes [%0], [%1], 2560, [%3];\n\t"
                         "cp.async.bulk.shared::cluster.global.mbarrier::complete_tx::bytes [%0+2560], [%2], 512, [%3];"
                         ::"r"(sb + OFF_WX), "l"(P.w_e + 512 * DD), "l"(P.w_x), "r"(sb + MB_H + 24) : "memory");
#pragma unroll
            for (int i = PACE; i < 4; i++) {
                mbar_wait(sb + MB_H + 8 * (i - PACE), 0);
                tma2d(sb + OFF_H + i * 10240, &tm_h, i * 64, n0, sb + MB_H + 8 * i);
            }
            mbar_wait(sb + MB_H + 16, 0);
            l2_prefetch(P.ea + cta * EPC, ne * 8);
            l2_prefetch((const char*)P.w_h + (cta & 127) * 2048, 2048);
            TIM(1);
#pragma unroll
            for (int k = 3; k >= 0; k--) {
                mbar_wait(sb + MB_B + 8 * k, 0);
                asm volatile("cp.async.bulk.tensor.2d.global.shared::cta.bulk_group [%0, {%2, %3}], [%1];"
                             ::"l"(&tm_b), "r"(sb + OFF_MT + k * 10240), "r"(k * 64), "r"(n0) : "memory");
            }
            TIM(8);
            asm volatile("cp.async.bulk.commit_group;\n\tcp.async.bulk.wait_group.read 0;" ::: "memory");
            mbar_arrive(sb + MB_BR);
            const uint32_t tgt = lds32(sb + OFF_BCNT + 92) * NCTA;
            TIM(17);
            asm volatile("cp.async.bulk.wait_group 0;" ::: "memory");
            TIM(18);
            if (TRED) asm volatile("fence.release.gpu;\n\tcp.reduce.async.bulk.global.shared::cta.bulk_group.add.u32 [%0], [%1], 16;\n\tcp.async.bulk.commit_group;"
                                   ::"l"(P.cnt), "r"(sb + OFF_ONE) : "memory");
            else asm volatile("red.release.gpu.global.add.u32 [%0],1;" ::"l"(P.cnt) : "memory");
            TIM(19);
            poll<NPB>(P.cnt, tgt);
            asm volatile("fence.acquire.gpu;" ::: "memory");
            mbar_arrive(sb + MB_GI);
        }
        __syncwarp();
    } else {
        if (wg * 4 + w < 15 && elect()) {
            const int i = wg * 4 + w;
            const uint32_t a = i < 11 ? sb + MB_W + 16 * i : sb + MB_V + 64 * (i - 11);
            mbar_init(a, i < 6 || i == 8 ? 1 : i < 8 ? 2 : i < 11 ? 4 : 66);
            mbar_init(a + 8, i < 6 ? 1 : i < 8 ? 2 : i == 8 ? 64 : i < 11 ? 4 : 16);
        }
        int ds[2] = {0, 0}, sr[2] = {0, 0}, own[2], r[2];
#pragma unroll
        for (int i = 0; i < 2; i++)
            if (tid + i * NR < ne) { ds[i] = __ldg(P.dst + cta * EPC + tid + i * NR); sr[i] = __ldg(P.src + cta * EPC + tid + i * NR); }
        uint32_t pv = 0;
        if (tid < 320) { if ((tid & 3) < 3 && (tid >> 2) < nvalid) pv = __ldg((const unsigned short*)P.pos + (n0 + (tid >> 2)) * 3 + (tid & 3)); }
        else if (tid == 320) pv = ld_rlx(P.cnt);
        sts32_gt(sb + OFF_OK + 4 * tid, tid >= 144 && tid < 164 ? (tid - 144) / 2 * RC : 0, 167, tid);
        bar_sync(5, NTHREADS);
        TIM(1);
#pragma unroll
        for (int i = 0; i < 2; i++) { own[i] = ds[i] / NPC; r[i] = atoms_inc(tid + i * NR < ne ? sb + OFF_CNT + 4 * own[i] : dum); }
#pragma unroll
        for (int i = 0; i < 2; i++)
            sts32_gt(sb + OFF_V + own[i] * 256 + 4 * (r[i] + (r[i] * 43 >> 7) + 1), (ds[i] - own[i] * NPC) | ((tid + i * NR) << 7) | (sr[i] << 18),
                     tid + i * NR < ne ? 48 : INT_MIN, r[i]);
        if (tid < 320) { asm volatile("st.shared.u16 [%0],%1;" ::"r"(sb + OFF_PD + 2 * tid), "r"(pv) : "memory"); sts32_gt(sb + OFF_OK + 24, 1, pv & 0x7fff, 0x3a80); }
        else if (tid == 320) { sts32(sb + OFF_BCNT + 92, pv / NCTA + 1); sts128(sb + OFF_SP + 80, make_uint4(0x3f803f80u, 0, 0, 0x3f803f80u)); }
        if (KA & 1) keep_alive(kz);
        TIM(13);
        bar_sync(5, NR);
        const uint32_t epoch = lds32(sb + OFF_BCNT + 92);
        const int o = tid >> 3, j = tid & 7, o1 = min(o + NR / 8, NCTA - 1);
        const uint32_t c0 = lds32(sb + OFF_CNT + 4 * o), c1 = lds32(sb + OFF_CNT + 4 * o1);
        uint4 p0 = lds128(sb + OFF_V + o * 256 + j * 16), p1 = lds128(sb + OFF_V + o1 * 256 + j * 16);
        p0.x = (epoch << 11) | c0;
        p1.x = (epoch << 11) | c1;
        uint4* g0 = &P.in[(o * NCTA + cta) * 8 + j];
        uint4* g1 = &P.in[(o1 * NCTA + cta) * 8 + j];
        st_pkt(g0, p0);
        if (tid < NCTA * 8 - NR) st_pkt(g1, p1);
        if (max(c0, c1) > 24) {
            uint4 x0 = lds128(sb + OFF_V + o * 256 + 128 + j * 16), x1 = lds128(sb + OFF_V + o1 * 256 + 128 + j * 16);
            x0.x = p0.x;
            x1.x = p1.x;
            st_pkt(g0 + NCTA * NCTA * 8, x0);
            st_pkt(g1 + NCTA * NCTA * 8, x1);
        }
        if (KA & 1) keep_alive(kz);
        TIM(2);
        const uint32_t tg = epoch << 11;
        const uint4* inb = &P.in[cta * NCTA * 8 + tid];
        auto sort_records = [&](auto between) {
        mbar_wait(sb + MB_HINT, 0);
        uint4 pk[2];
        pk[0] = ld_pkt(inb);
        pk[1] = ld_pkt(tid < NCTA * 8 - NR ? inb + NR : inb);
        between();
#pragma unroll 1
        for (int k = 0; k < SPIN && ((pk[0].x ^ tg) | (pk[1].x ^ tg)) >= 2048; k++) {
            pk[0] = ld_pkt(inb);
            pk[1] = ld_pkt(tid < NCTA * 8 - NR ? inb + NR : inb);
        }
        if (tid >= NCTA * 8 - NR) pk[1].x = 0;
        __syncwarp();
        TIM(3);
        int n[2], ps[6];
#pragma unroll
        for (int i = 0; i < 2; i++) {
            n[i] = (pk[i].x & 2047) - 3 * (tid & 7);
            ps[3 * i] = atoms_inc(n[i] > 0 ? sb + OFF_BCNT + (pk[i].y & 0x78) : dum);
            ps[3 * i + 1] = atoms_inc(n[i] > 1 ? sb + OFF_BCNT + (pk[i].z & 0x78) : dum);
            ps[3 * i + 2] = atoms_inc(n[i] > 2 ? sb + OFF_BCNT + (pk[i].w & 0x78) : dum);
        }
        if (KA & 2) { kz &= ps[5]; keep_alive(kz); }
#pragma unroll
        for (int i = 0; i < 2; i++) {
            const uint32_t r[3] = {pk[i].y, pk[i].z, pk[i].w};
#pragma unroll
            for (int k = 0; k < 3; k++) {
                const int p = min(ps[3 * i + k], CAP - 1);
                sts32_gt(sb + OFF_REC + 4 * p, r[k], n[i], k);
                sts8_gt(sb + OFF_PRD + p, (tid + i * NR) >> 3, n[i], k);
            }
        }
        if (max(n[0], n[1]) > 24) {
#pragma unroll 1
            for (int i = 0; i < 2; i++) {
                const int m = (i ? n[1] : n[0]) - 24;
                if (m <= 0) continue;
                const uint4* q2 = inb + i * NR + NCTA * NCTA * 8;
                uint4 x = ld_pkt(q2);
                for (int k = 0; k < SPIN && (x.x ^ tg) >= 2048; k++) x = ld_pkt(q2);
                if ((x.x & 2047) > 48) sts32(sb + OFF_BCNT + 84, 1);
#pragma unroll 1
                for (int k = 0; k < min(3, m); k++) {
                    const uint32_t r = k == 0 ? x.y : k == 1 ? x.z : x.w;
                    const int p = min((int)atoms_inc(sb + OFF_BCNT + (r & 0x78)), CAP - 1);
                    sts32(sb + OFF_REC + 4 * p, r);
                    sts8_gt(sb + OFF_PRD + p, (tid + i * NR) >> 3, 1, 0);
                }
            }
        }
        };
        if (wg < 4) {
            asm volatile("bar.arrive 8, %0;" ::"n"(NR) : "memory");
            static_for<0, 4>(chunk);
            sort_records([&]() { static_for<4, 4 + EARLY>(chunk); if (EARLY < 4) { wg_wait<EARLY - 1>(); retire(std::integral_constant<int, 4>{}); } });
            if (EARLY < 4) { wg_wait<0>(); pin<40>(acc); }
            if (EARLY == 3) retire(std::integral_constant<int, 5>{});
        } else {
            bar_sync(8, NR);
            if (t128 == 0) {
                asm volatile("red.relaxed.gpu.global.add.u32 [%0],1;" ::"l"(P.cnt + 4) : "memory");
                poll<NPH>(P.cnt + 4, epoch * NCTA);
            }
            if (w) {
                const uint32_t nr = 80 | ((n0 + (lane & 7) * 4) << 18), np = cta * 0x01010101u;
#pragma unroll
                for (int i = 0; i < CAP / 256; i++) sts128(sb + OFF_REC + 16 * (t128 - 32) + 1024 * i, make_uint4(nr, nr + (1 << 18), nr + (2 << 18), nr + (3 << 18)));
#pragma unroll
                for (int i = 0; i < 3; i++) sts128(sb + OFF_PRD + 16 * (t128 - 32) + 640 * i, make_uint4(np, np, np, np));
                if (t128 == 32) { sts32(sb + OFF_PD + 8 * 80, 0); sts32(sb + OFF_PD + 8 * 80 + 4, 0); }
                if (w == 2 && elect()) {
                    mbar_wait(sb + MB_H + 16, 0);
                    fence_async();
                    mbar_expect(sb + MB_WL, 32768);
#pragma unroll
                    for (int k = 0; k < 4; k++) tma2d(sb + OFF_V + k * 8192, &tm_we, k * 64, 192, sb + MB_WL);
                }
            }
            arrive_one(sb + MB_HINT);
            TIM(12);
            sort_records([]() {});
        }
        arrive_one(sb + MB_META);
    }
    TIM(5);

    if (wg == 4) {
        asm volatile("setmaxnreg.dec.sync.aligned.u32 %0;" ::"n"(REG_AUX));
        mbar_wait(sb + MB_META, 0);
        int nt, mystart, st1, gbase = 0;
        auto bucket_scan = [&](int rc) {
            int c[10], mx = 0;
#pragma unroll
            for (int i = 0; i < 5; i++) { const uint4 x = lds128(sb + OFF_BCNT + 16 * i); c[2 * i] = x.x - 2 * i * rc; c[2 * i + 1] = x.z - (2 * i + 1) * rc; }
            int st = 0, lim = 32;
            mystart = lane ? 0x7fffffff : 0;
#pragma unroll
            for (int b = 0; b < 9; b++) {
                st = max(st + c[b], lim);
                lim = (st | 31) + 65;
                mx = max(mx, c[b]);
                if (lane == b + 1) mystart = st;
                if (b == 0) st1 = st;
            }
            nt = max(st + c[9] + 31, lim - 32) >> 5;
            asm volatile("{.reg .pred p; setp.lt.u32 p,%3,10; @p st.shared.v2.u32 [%0],{%1,%2};}"
                         ::"r"(sb + OFF_SP + 8 * (t128 - 65)), "r"(min((mystart >> 5) - 1, nt) + 2), "r"((mystart >> 5) + 3), "r"(t128 - 65) : "memory");
            return max(mx, c[9]);
        };
        const bool fast = bucket_scan(RC) <= RC - 4 && lds32(sb + OFF_BCNT + 84) == 0;
        if (!fast) {
            bar_sync(5, 128);
            if (t128 < 23) sts32(sb + OFF_BCNT + 4 * t128, 0);
            bar_sync(5, 128);
            int below = 0;
#pragma unroll 2
            for (int e = t128; e < NE; e += 128) {
                const int l = __ldg(P.dst + e) - n0;
                below += l < 0;
                if (l >= 0 && l < NPC) reds_inc(sb + OFF_BCNT + (l & 0x78));
            }
            asm volatile("red.shared.add.u32 [%0],%1;" ::"r"(sb + OFF_BCNT + 88), "r"(below) : "memory");
            bar_sync(5, 128);
            bucket_scan(0);
            gbase = lds32(sb + OFF_BCNT + 88) + cta * 1280;
            sts32_gt(sb + OFF_BCNT + 4 + 8 * t128, mystart, 10, t128);
#pragma unroll 1
            for (int i = t128; i < nt * 32 + 256; i += 128) g_sidx[gbase + i] = 80u << 18;
            bar_sync(5, 128);
#pragma unroll 2
            for (int e = t128; e < NE; e += 128) {
                const int l = __ldg(P.dst + e) - n0;
                if (l >= 0 && l < NPC) g_sidx[gbase + atoms_inc(sb + OFF_BCNT + 4 + (l & 0x78))] = e | (l << 18);
            }
            bar_sync(5, 128);
        }
        TIM(4);
        auto feed = [&](auto fastc) {
            constexpr bool FAST = decltype(fastc)::value;
            struct Tile { uint32_t rec, s0, s1; uint2 ea; int bb; } x;
            const uint32_t* posw = (const uint32_t*)P.pos;
            const uint2* eap = P.ea;
            auto locate = [&](int t, int& b, int& sb1, int& d1, int& d0, bool head) {
                if (head) {
                    b = (st1 >> 5) <= t; sb1 = b ? st1 : 0; d1 = b ? RC - st1 : 0; d0 = 0;
                    return;
                }
                b = __popc(__ballot_sync(~0u, (mystart >> 5) <= t)) - 1;
                sb1 = __shfl_sync(~0u, mystart, b);
                d1 = b * RC - sb1;
                d0 = (b - 1) * RC - __shfl_sync(~0u, mystart, b - 1);
            };
            auto fetch = [&](Tile& x, int t, bool head = false) {
                int b, s1b, d1, d0, fp = t * 32 + (lane & 7) * 4 + (lane >> 3);
                locate(t, b, s1b, d1, d0, head);
                x.bb = (s1b >> 5) == t ? -b : b;
                uint32_t e, rec;
                if (FAST) { fp += fp < s1b ? d0 : d1; rec = lds32(sb + OFF_REC + 4 * fp); e = lds8(sb + OFF_PRD + fp) * EPC + ((rec >> 7) & 2047); }
                else { const uint32_t y = g_sidx[gbase + fp]; e = y & 0x3ffff; rec = (y >> 18) | (__ldg(P.src + e) << 18); }
                x.rec = rec;
                asm volatile("ld.global.v2.u32 {%0,%1},[%4]; ld.global.u32 %2,[%5]; ld.global.u32 %3,[%5+4];"
                             : "=r"(x.ea.x), "=r"(x.ea.y), "=r"(x.s0), "=r"(x.s1) : "l"(eap + e), "l"(posw + ((rec >> 18) * 3 >> 1)) : "memory");
            };
            auto prep = [&](Tile& x) {
                const uint32_t loc = x.rec & 127, sh = (x.rec >> 14) & 16;
                const uint2 d = lds64(sb + OFF_PD + 8 * loc), ea = x.ea;
                const uint32_t dxy = hsub2(d.x, __funnelshift_r(x.s0, x.s1, sh)), dz = hsub2(d.y, x.s1 >> sh), sq = hmul2(dxy, dxy);
                x.s0 = packh(bflo(dxy), bfhi(dxy));
                x.s1 = packh(rbf(bflo(sq) + bfhi(sq) + bflo(hmul2(dz, dz))), bflo(ea.x));
                x.ea.x = packh(bfhi(ea.x), bflo(ea.y));
                x.ea.y = packh(bfhi(ea.y), bflo(dz));
                x.rec = loc - 8 * abs(x.bb);
            };
            auto planes = [&](const Tile& x, uint32_t va, int stride, bool on) {
                const uint32_t vv[4] = {0x3800u, x.s0, x.s0 >> 16, x.ea.y >> 16};
#pragma unroll
                for (int c = 0; c < 4; c++) sts128(va + c * stride, make_uint4(0, 0, 0, 0));
#pragma unroll
                for (int c = 0; c < 4; c++) sts16(va + c * stride + 2 * (x.rec & 7), on ? vv[c] : 0);
            };
            auto store = [&](const Tile& x, int u) {
                const uint32_t va = sb + OFF_PL + (u & 7) * 512 + lane * 16;
                sts128(va, make_uint4(x.s1, x.ea.x, x.ea.y, 0));
                planes(x, va + 4096, 4096, x.rec < 8);
                if (x.bb < 0) planes(x, sb + OFF_EV + 512 + (~x.bb & 3) * 2048 + lane * 16, 512, x.rec + 8 < 8);
            };
            auto build = [&](Tile& x, int u) {
                prep(x);
                mbar_wait(mbv((u >> 1) + 1) + 8, (((u >> 1) + 1) >> 2) & 1);
                store(x, u);
                fence_async();
                arrive_one(mbv(u >> 1));
            };
            const int ng = (nt + 1) >> 1, par = w >> 1;
            const char* gB = (const char*)P.B + (lane & 7) * 16;
            const uint32_t r = lane >> 3, dst0 = sb + OFF_W + (w & 1) * 4096 + r * 128 + (((lane & 7) ^ r) << 4);
            uint4 s[2];
            auto rows = [&](int p, bool head = false) {
                int b, s1b, d1, d0;
                if (FAST) locate(2 * p + (w & 1), b, s1b, d1, d0, head);
#pragma unroll
                for (int hh = 0; hh < 2; hh++) {
                    const int p0 = p * 64 + (w & 1) * 32 + hh * 16 + r * 4;
                    if (FAST) {
                        const uint32_t x0 = sb + OFF_REC + 4 * (p0 - hh * 16 + d0), x1 = sb + OFF_REC + 4 * (p0 - hh * 16 + d1);
                        const int kk = s1b - (p0 - hh * 16);
                        s[hh] = make_uint4(lds32((hh * 16 < kk ? x0 : x1) + hh * 64), lds32((hh * 16 + 1 < kk ? x0 : x1) + hh * 64 + 4),
                                           lds32((hh * 16 + 2 < kk ? x0 : x1) + hh * 64 + 8), lds32((hh * 16 + 3 < kk ? x0 : x1) + hh * 64 + 12));
                    }
                    else s[hh] = make_uint4(__ldg(P.src + (g_sidx[gbase + p0] & 0x3ffff)) << 18, __ldg(P.src + (g_sidx[gbase + p0 + 1] & 0x3ffff)) << 18,
                                            __ldg(P.src + (g_sidx[gbase + p0 + 2] & 0x3ffff)) << 18, __ldg(P.src + (g_sidx[gbase + p0 + 3] & 0x3ffff)) << 18);
                }
            };
            auto gather = [&](int p, auto ns) {
                constexpr int NS = decltype(ns)::value;
#pragma unroll
                for (int hh = 0; hh < 2; hh++) {
                    uint32_t dst = (dst0 ^ (hh * 64)) + ((p & 3) << 15);
                    if (hh) { cp_row<512, NS>(dst, gB, s[1].x >> 18); cp_row<1536, NS>(dst, gB, s[1].y >> 18); cp_row<2560, NS>(dst, gB, s[1].z >> 18); cp_row<3584, NS>(dst, gB, s[1].w >> 18); }
                    else { cp_row<0, NS>(dst, gB, s[0].x >> 18); cp_row<1024, NS>(dst, gB, s[0].y >> 18); cp_row<2048, NS>(dst, gB, s[0].z >> 18); cp_row<3072, NS>(dst, gB, s[0].w >> 18); }
                }
                asm volatile("cp.async.mbarrier.arrive.noinc.shared.b64 [%0];" ::"r"(NS == 0 && p == 0 ? sb + MB_G0 : mbv(p)) : "memory");
            };
            if (!par) {
                rows(1, true);
                const uint4 s2[2] = {s[0], s[1]};
                rows(0, true);
                TIM(9);
                mbar_wait(mbv(0) + 8, 0);
                mbar_wait(mbv(1) + 8, 0);
                mbar_wait(sb + MB_GI, 0);
                TIM(14);
                gather(0, std::integral_constant<int, 0>{});
                s[0] = s2[0];
                s[1] = s2[1];
                gather(1, std::integral_constant<int, 0>{});
                TIM(15);
                rows(2);
                mbar_wait(mbv(2) + 8, 0);
                gather(2, std::integral_constant<int, 0>{});
            } else if (w == 2) {
                Tile y[3];
#pragma unroll
                for (int i = 0; i < 3; i++) fetch(y[i], i, true);
                fetch(x, 3, true);
#pragma unroll
                for (int i = 0; i < 3; i++) prep(y[i]);
                sts32_gt(dum, y[0].s1 ^ y[1].s1 ^ y[2].s1, gridDim.x, NCTA);
                mbar_wait(sb + MB_VF, 0);
#pragma unroll
                for (int c = 0; c < 6; c++) sts128(sb + OFF_PL + c * 4096 + lane * 16, make_uint4(0, 0, 0, 0));
#pragma unroll
                for (int i = 0; i < 3; i++) store(y[i], i + 1);
                fence_async();
                __syncwarp();
                if (elect()) asm volatile("mbarrier.arrive.shared.b64 _, [%0], 66;\n\tmbarrier.arrive.shared.b64 _, [%1], 2;" ::"r"(mbv(0)), "r"(mbv(1)) : "memory");
                mbar_wait(sb + MB_GI, 0);
                TIM(16);
            }
            int p = 4 - par;
            if (w != 2) fetch(x, 2 * p - 3 + (w & 1));
#pragma unroll 1
            for (; p < ng; p += 2) {
                rows(p);
                build(x, 2 * p - 2 + (w & 1));
                gather(p, std::integral_constant<int, NSG>{});
                fetch(x, 2 * p + 1 + (w & 1));
            }
            build(x, 2 * p - 2 + (w & 1));
#pragma unroll 1
            for (; p < ng + 4; p += 2) {
                const uint32_t mb = mbv(p);
                mbar_wait(mb + 8, (p >> 2) & 1);
                if (elect()) {
                    if (p < ng + 2) asm volatile("mbarrier.arrive.shared.b64 _, [%0], %1;" ::"r"(mb), "r"(32 + p - ng) : "memory");
                    const int c = p - ng;
                    fence_async();
                    mbar_expect(sb + MB_W2 + 8 * c, 16384);
#pragma unroll
                    for (int k = 0; k < 2; k++)
                        tma2d(sb + OFF_W + (2 * (w & 1) + k) * 8192 + ((p & 3) << 15), &tm_wh, (2 * (w & 1) + k) * 64, 256 + 64 * c, sb + MB_W2 + 8 * c);
                }
                __syncwarp();
            }
        };
        if (fast) feed(std::true_type{}); else feed(std::false_type{});
        TIM(6);
        const uint2 pd = lds64(sb + OFF_PD + 8 * min(t128, 80));
        bar_sync(6, NTHREADS);
        bool bad = t128 < 7 && lds32(sb + OFF_OK + 4 * t128) == 0;
        if (t128 < nvalid) {
            float x = bflo(pd.x), y = bfhi(pd.x), z = bflo(pd.y);
            const float4* u = P.U + cta * 16 * 80 + t128;
#pragma unroll
            for (int k0 = 0; k0 < 16; k0 += 8) {
                float4 v[8];
#pragma unroll
                for (int k = 0; k < 8; k++) v[k] = __ldcg(u + (k0 + k) * 80);
#pragma unroll
                for (int k = 0; k < 8; k++) { x += v[k].x; y += v[k].y; z += v[k].z; }
            }
            __nv_bfloat16* o = P.out + NN * DD + (n0 + t128) * 3;
            o[0] = __float2bfloat16(x); o[1] = __float2bfloat16(y); o[2] = __float2bfloat16(z);
            bad |= !(fabsf(x) + fabsf(y) + fabsf(z) < INFINITY);
        }
        TIM(7);
        TIMDUMP();
        bar_or(8, bad);
    } else {
        const uint32_t frag = mtb + (w * 16 + g) * 16 + q * 4;
        const uint32_t row_off = (t128 >> 3) * 128 + (((t128 & 7) ^ ((t128 >> 3) & 7)) << 4);
        const int grow = (n0 + (t128 >> 3)) * 32 + wg * 8 + (t128 & 7), rleft = nvalid - (t128 >> 3);
        static_for<4 + EARLY, 12>(chunk);
        asm volatile("setmaxnreg.inc.sync.aligned.u32 %0;" ::"n"(REG_CON));
        const uint32_t wxa = sb + OFF_WX + 2 * (wg * 64 + w * 16 + g), wea = wxa + 1024 * min(q, 2);
        uint32_t wf[6] = {lds16(wea), lds16(wea + 512), lds16(wea + 16), lds16(wea + 528), lds16(wxa + 2560), lds16(wxa + 2576)};
        if (q == 3) wf[0] = wf[2] = 0;
        if (q >= 2) wf[1] = wf[3] = 0;
        uint32_t WA[4] = {packh(0.5f * bflo(wf[0]), 0.5f * bflo(wf[1])), packh(0.5f * bflo(wf[2]), 0.5f * bflo(wf[3])), a0, a1};
        const float wx0 = bflo(wf[4]), wx1 = bflo(wf[5]);
        sts32_gt(sb + OFF_OK + 8 * q, 1, WA[0] & 0x7000, 0);
        sts32_gt(sb + OFF_OK + 8 * q + 4, 1, WA[0] & 0x70000000, 0);
        bool bad = max(max(wf[0] & 0x7fff, wf[1] & 0x7fff), max(wf[2] & 0x7fff, wf[3] & 0x7fff)) > 0x4300;
        TIM(6);

        auto init_s = [&](uint32_t* s, uint32_t a) { ldsm4t(s, a); ldsm4t(s + 4, a + 2048); pin<8>(s); };
        uint32_t S0[8], S1[8];
        float T[16] = {};
        uint32_t P0[8], P1[8] = {};
        uint32_t mptr = frag, sp = 0, u3[3];
        const float4* ub = P.U + (cta * 16 + wg * 4 + w) * 80 + g;
        asm volatile("" : "+l"(ub));
        const uint32_t zero = gridDim.x - NCTA;
        const uint2 oh = lds64(sb + OFF_SP + 80 + 8 * (g & 1));
        auto flush1 = [&]() {
            sts32(mptr, pack(T[0], T[1]));
            sts32(mptr + 128, pack(T[2], T[3]));
#pragma unroll
            for (int d = 0; d < 3; d++) u3[d] = pack(fmaf(wx1, T[4 * d + 6], wx0 * T[4 * d + 4]), fmaf(wx1, T[4 * d + 7], wx0 * T[4 * d + 5]));
            pin<3>(u3);
            pin<16>(T);
            mptr += 1024;
        };
        auto flush2 = [&]() {
            float4 c;
            asm volatile("mma.sync.aligned.m16n8k16.row.col.f32.bf16.bf16.f32 {%0,%1,%2,%3},{%4,%5,%6,%7},{%8,%9},{%10,%10,%10,%10};"
                         : "=f"(c.x), "=f"(c.y), "=f"(c.z), "=f"(c.w) : "r"(movm(u3[0])), "r"(movm(u3[2])), "r"(movm(u3[1])), "r"(0u), "r"(oh.x), "r"(oh.y), "f"(0.f));
            asm volatile("st.global.v4.f32 [%4],{%0,%1,%2,%3};" ::"f"(c.x), "f"(c.y), "f"(c.z), "f"(c.w), "l"(ub) : "memory");
            ub += 8;
        };
        auto act = [&](uint32_t* s, uint32_t* p, int lo, int hi) {
#pragma unroll
            for (int i = lo; i < hi; i++) p[i] = silu_half_h2(s[i]);
        };
        constexpr uint32_t vd0 = ((sb + OFF_PL + 4096) >> 4) | (8 << 16), ev0 = (sb + OFF_EV) >> 4;
        uint64_t fd[2], va[2], vb[2];
#pragma unroll
        for (int i = 0; i < 2; i++) {
            fd[i] = (((sb + OFF_PL) >> 4) | (256 << 16) | (8ull << 32)) + 32 * i + ((uint64_t)(zero << i) << 32);
            va[i] = (vd0 | (256ull << 32)) + 32 * i + ((uint64_t)(zero << i) << 32);
            vb[i] = (vd0 | (256ull << 32)) + 32 * i + 16 + ((uint64_t)(zero << (i + 2)) << 32);
        }
        uint32_t mask = 64, gmask = 32768, gld = wbase + stm_off;
        auto xor64 = [](uint64_t& d, uint32_t m) { asm volatile("{.reg .b32 l, h; mov.b64 {l,h},%0; xor.b32 l,l,%1; mov.b64 %0,{l,h};}" : "+l"(d) : "r"(m)); };
        int t = 2, nxt;
        bool plain, rdy = false;
        auto step = [&](auto kind, auto odd, uint32_t* sc, uint32_t* sn, uint32_t* pn, uint32_t* pp) {
            constexpr int KIND = decltype(kind)::value, ODD = decltype(odd)::value;
            const uint32_t evo = 32 + ((sp << 4) & 384);
            uint32_t NA[4];
            if (KIND) { sp += 4; nxt = lds32(sb + OFF_SP + sp); }
            if (KIND == 1) {
                NA[0] = WA[0] ^ zero; NA[1] = WA[1] ^ zero;
                NA[2] = lds32(mptr + 1024);
                NA[3] = lds32(mptr + 1024 + 128);
                pin<4>(NA);
            }
            wg_fence();
            if (KIND == 2) {
                wrs32<1>(T, pp, (ev0 + (8 << 16) + evo) | (32ull << 32));
                wrs32h(sn, WA, fd[ODD]);
                wrs32<1>(T, pp + 4, (ev0 + (8 << 16) + 16 + evo) | (32ull << 32));
            } else {
                if (KIND == 1) wrs32h(sn, NA, fd[ODD]);
                wrs32<1>(T, pp, va[ODD]);
                wrs32h(sn, WA, KIND == 1 ? (ev0 + (evo << 16)) | (8ull << 32) : fd[ODD]);
                wrs32<1>(T, pp + 4, vb[ODD]);
            }
            wg_commit();
            t++;
            plain = t != nxt;
            act(sc, pn, 0, 4);
            if (KIND == 2) {
                pin<4>(pn);
                wg_wait<0>();
                pin<16>(T);
                flush1();
                wg_fence();
                wrs32<0>(T, pp, va[ODD]);
                wrs32<1>(T, pp + 4, vb[ODD]);
                wg_commit();
            }
            const uint32_t done = (uint32_t)va[1] + (sb + MB_V + 8 - 32 - vd0), ga = gld + 4096 * ODD;
            xor64(va[ODD], mask); xor64(vb[ODD], mask); xor64(fd[ODD], mask ^ 128);
            if (ODD) {
                asm volatile("xor.b32 %0,%0,128; xor.b32 %1,%1,65536;" : "+r"(mask), "+r"(gmask));
                rdy = mbar_try((uint32_t)va[0] + (sb + MB_V - vd0), t >> 3);
            }
            act(sc, pn, 4, 8);
            if (KIND == 2) flush2();
            pin<8>(pn);
            init_s(sc, ga);
            wg_wait<0>();
            if (ODD) {
                asm volatile("{.reg .pred p; setp.eq.u32 p,%1,0; @p mbarrier.arrive.shared.b64 _, [%0];}" ::"r"(done), "r"(lane) : "memory");
                gld ^= gmask;
            }
            pin<8>(sn);
            pin<16>(T);
            pin<8>(pp);
            if (KIND == 1) { pin<4>(WA); pin<4>(NA); WA[2] = NA[2] ^ zero; WA[3] = NA[3] ^ zero; }
        };
        using K0 = std::integral_constant<int, 0>;
        using K1 = std::integral_constant<int, 1>;
        using K2 = std::integral_constant<int, 2>;
        mbar_wait(sb + MB_G0, 0);
        init_s(S0, gld);
        init_s(S1, gld + 4096);
        pin<4>(WA);
        pin<16>(T);
        pin<8>(P1);
        if (KA & 4) mbar_wait_ka(mbv(0), 0, kz); else mbar_wait(mbv(0), 0);
        arrive_one(mbv(0) + 8);
        wg_fence();
        wrs32h(S0, WA, fd[1]);
        wg_commit();
        nxt = lds32(sb + OFF_SP + sp);
        bad |= kz != 0;
        fd[0] ^= 64;
        fd[1] ^= 64;
        gld ^= 32768;
        wg_wait<0>();
        pin<8>(S0);
        plain = nxt != 2;
        TIM(8);
        auto last = [&](uint32_t* p, int i) { wg_fence(); wrs32<1>(T, p, va[i]); wrs32<1>(T, p + 4, vb[i]); wg_commit(); wg_wait<0>(); pin<16>(T); };
        for (;;) {
            if (!rdy) mbar_wait((uint32_t)va[0] + (sb + MB_V - vd0), t >> 3);
            if (plain) step(K0{}, K0{}, S0, S1, P0, P1);
            else if (sp & 4) step(K2{}, K0{}, S0, S1, P0, P1);
            else if (sp != 72) step(K1{}, K0{}, S0, S1, P0, P1);
            else { last(P1, 0); break; }
            if (plain) step(K0{}, K1{}, S1, S0, P1, P0);
            else if (sp & 4) step(K2{}, K1{}, S1, S0, P1, P0);
            else if (sp != 72) step(K1{}, K1{}, S1, S0, P1, P0);
            else { last(P0, 1); break; }
        }
        TIM(7);
        flush1();
        fence_async();
        flush2();
#pragma unroll
        for (int j = 0; j < 20; j++) { acc[2 * j] = bflo(Cp[j]); acc[2 * j + 1] = bfhi(Cp[j]); }
        pin<40>(acc);
        TIM(9);
        if (wg < 3) asm volatile("bar.arrive 6, %0;" ::"n"(NTHREADS) : "memory");
        auto wk = [&](int i) { return wbase + (((((nxt - 1) >> 1) + wg + i) & 3) << 15); };
        auto mk = [&](int i) { return ((sb + OFF_MT + ((wg + i) & 3) * 10240) >> 4) | (8 << 16); };
#pragma unroll
        for (int k = 0; k < 4; k++) mbar_wait(sb + MB_W2 + 8 * k, 0);
        bar_sync(1 + wg, 128);
        gemm_chunk<1, 0>(acc, wk(0) >> 4, mk(0));
        wg_wait<0>();
        pin<40>(acc);
        uint4 hr[5];
#pragma unroll
        for (int i = 0; i < 5; i++) hr[i] = ldg128_gt(P.h + grow + 512 * i, rleft, 16 * i);
        if (wg < 3) bar_sync(10 + wg, 256); else bar_sync(6, NTHREADS);
        TIM(10);
#pragma unroll
        for (int k = 0; k < 3; k++) gemm_chunk<1, 0>(acc, wk(k + 1) >> 4, mk(k + 1));
        if (wg) asm volatile("bar.arrive %0, %1;" ::"r"(9 + wg), "r"(256) : "memory");
        wg_wait<0>();
        pin<40>(acc);
        TIM(11);
        bar_sync(1 + wg, 128);
#pragma unroll
        for (int j = 0; j < 20; j++) Cp[j] = pack(silu_half(acc[2 * j]), silu_half(acc[2 * j + 1]));
#pragma unroll
        for (int j = 0; j < 5; j++) stsm4t(wbase + stm_off + (j < 4 ? j * 2048 : 32768), Cp[4 * j], Cp[4 * j + 1], Cp[4 * j + 2], Cp[4 * j + 3]);
        TIM(13);
        bar_sync(1 + wg, 128);
        TIM(14);
#pragma unroll
        for (int i = 0; i < 5; i++) {
            const uint4 y = lds128(wbase + row_off + (i < 4 ? i * 2048 : 32768)), h = hr[i];
            if (16 * i < rleft) ((uint4*)P.out)[grow + 512 * i] = make_uint4(hadd2(h.x, y.x), hadd2(h.y, y.y), hadd2(h.z, y.z), hadd2(h.w, y.w));
        }
        TIM(12);
        TIMDUMP();
        if (wg == 3) {
            uint32_t a = 0;
#pragma unroll
            for (int j = 0; j < 10; j++) asm("fma.rn.bf16x2 %0,%1,%2,%0;" : "+r"(a) : "r"(Cp[2 * j]), "r"(zero));
            bad |= (a & 0x7fff7fffu) != 0;
        }
        if (bar_or(8, bad)) fallback(P, smem, n0, nvalid);
    }
}

typedef CUresult (*EncodeFn)(CUtensorMap*, CUtensorMapDataType, cuuint32_t, void*, const cuuint64_t*, const cuuint64_t*,
                             const cuuint32_t*, const cuuint32_t*, CUtensorMapInterleave, CUtensorMapSwizzle,
                             CUtensorMapL2promotion, CUtensorMapFloatOOBfill);

void encode(EncodeFn fn, CUtensorMap* m, const void* p, int rows, int box_rows) {
    cuuint64_t dims[2] = {(cuuint64_t)DD, (cuuint64_t)rows}, strides[1] = {DD * 2};
    cuuint32_t box[2] = {64, (cuuint32_t)box_rows}, es[2] = {1, 1};
    fn(m, CU_TENSOR_MAP_DATA_TYPE_BFLOAT16, 2, const_cast<void*>(p), dims, strides, box, es, CU_TENSOR_MAP_INTERLEAVE_NONE,
       CU_TENSOR_MAP_SWIZZLE_128B, CU_TENSOR_MAP_L2_PROMOTION_L2_128B, CU_TENSOR_MAP_FLOAT_OOB_FILL_NONE);
}

}

extern "C" void kernel_launch(void* const* d_in, const int* in_sizes, int n_in, void* d_out, int out_size) {
    static EncodeFn fn = nullptr;
    static void *pB, *pIn, *pU, *pCnt;
    if (!fn) {
        void* p = nullptr;
        cudaDriverEntryPointQueryResult st;
        cudaGetDriverEntryPoint("cuTensorMapEncodeTiled", &p, cudaEnableDefault, &st);
        fn = (EncodeFn)p;
        cudaGetSymbolAddress(&pB, g_B);
        cudaGetSymbolAddress(&pIn, g_in);
        cudaGetSymbolAddress(&pU, g_U);
        cudaGetSymbolAddress(&pCnt, g_cnt);
        cudaFuncSetAttribute(egnn_kernel, cudaFuncAttributeMaxDynamicSharedMemorySize, SMEM_BYTES + TIMX);
    }
    CUtensorMap tm_h, tm_we, tm_wh, tm_b;
    encode(fn, &tm_b, pB, NN, NPC);
    encode(fn, &tm_h, d_in[0], NN, 80);
    encode(fn, &tm_we, d_in[5], 2 * DD + 5, 64);
    encode(fn, &tm_wh, d_in[7], 2 * DD, 64);
    Params P;
    P.pos = (const __nv_bfloat16*)d_in[1];
    P.ea = (const uint2*)d_in[2];
    P.src = (const int*)d_in[3];
    P.dst = (const int*)d_in[4];
    P.w_e = (const __nv_bfloat16*)d_in[5];
    P.w_x = (const __nv_bfloat16*)d_in[6];
    P.w_h = (const __nv_bfloat16*)d_in[7];
    P.out = (__nv_bfloat16*)d_out;
    P.h = (const uint4*)d_in[0];
    P.cnt = (uint32_t*)pCnt;
    P.in = (uint4*)pIn;
    P.B = (const uint4*)pB;
    P.U = (float4*)pU;
    egnn_kernel<<<NCTA, NTHREADS, SMEM_BYTES + TIMX, cudaStreamPerThread>>>(P, tm_h, tm_we, tm_wh, tm_b);
}
```
